```python
import torch

def _softmax(x, axis=-1):
    return torch.softmax(x, dim=axis)
def _gelu(x):
    return torch.nn.functional.gelu(x, approximate="tanh")
def _silu(x):
    return torch.nn.functional.silu(x)
def _sigmoid(x):
    return torch.sigmoid(x)
def _layernorm(x, axis=-1, eps=1e-5):
    m = x.mean(dim=axis, keepdim=True)
    v = x.var(dim=axis, keepdim=True, unbiased=False)
    return (x - m) / torch.sqrt(v + eps)
def _scatter_add(tgt, idx, src, axis=0):
    return tgt.clone().index_add_(axis, idx, src)
def _segment_sum(src, seg, n):
    out = torch.zeros((n,) + src.shape[1:], dtype=src.dtype)
    return out.index_add_(0, seg, src)
def _pad(x, pw):
    flat = tuple(v for pair in reversed(pw) for v in pair)
    return torch.nn.functional.pad(x, flat)

kernel_name = 'concat_heads__mha_block_cached__mha_block_cached__near_ridge'

def setup_inputs():

    _w = (lambda a: (lambda t: t.to(torch.bfloat16) if t.is_floating_point() else t)(torch.as_tensor(a)))
    def _A_setup():
        B, Sq, D = 16, 32, 1024
        H, Sk, Dh = 32, 32, 128
        return {
            "x": _w((lambda *s: torch.randn(*s, dtype=torch.bfloat16) * 0.8)(B, Sq, D)),
            "k_cache": _w((lambda *s: torch.randn(*s, dtype=torch.bfloat16) * 0.8)(B, H, Sk, Dh)),
            "v_cache": _w((lambda *s: torch.randn(*s, dtype=torch.bfloat16) * 0.05)(B, H, Sk, Dh)),
            "wq": _w((lambda *s: torch.randn(*s, dtype=torch.bfloat16) * 0.8)(D, H * Dh) * (D ** -0.5)),
            "wo": _w((lambda *s: torch.randn(*s, dtype=torch.bfloat16) * 0.05)(H * Dh, D) * ((H * Dh) ** -0.5)),
        }
    _A_in = _A_setup()

    def _B_setup():
        B, Sq, D = 16, 32, 1024
        H, Sk, Dh = 32, 32, 128
        return {
            "x": _w((lambda *s: torch.randn(*s, dtype=torch.bfloat16) * 0.8)(B, Sq, D)),
            "k_cache": _w((lambda *s: torch.randn(*s, dtype=torch.bfloat16) * 0.8)(B, H, Sk, Dh)),
            "v_cache": _w((lambda *s: torch.randn(*s, dtype=torch.bfloat16) * 0.05)(B, H, Sk, Dh)),
            "wq": _w((lambda *s: torch.randn(*s, dtype=torch.bfloat16) * 0.8)(D, H * Dh) * (D ** -0.5)),
            "wo": _w((lambda *s: torch.randn(*s, dtype=torch.bfloat16) * 0.05)(H * Dh, D) * ((H * Dh) ** -0.5)),
        }
    _B_in = _B_setup()

    return {
        "A_x": _A_in["x"],
        "A_k_cache": _A_in["k_cache"],
        "A_v_cache": _A_in["v_cache"],
        "A_wq": _A_in["wq"],
        "A_wo": _A_in["wo"],
        "B_x": _B_in["x"],
        "B_k_cache": _B_in["k_cache"],
        "B_v_cache": _B_in["v_cache"],
        "B_wq": _B_in["wq"],
        "B_wo": _B_in["wo"],
    }

def reference(A_x, A_k_cache, A_v_cache, A_wq, A_wo, B_x, B_k_cache, B_v_cache, B_wq, B_wo):
    def _A_ref(x, k_cache, v_cache, wq, wo):
        B, Sq, D = x.shape
        H, Dh = 32, 128
        q = (lambda x, *d: x.permute(*d))((x @ wq).reshape(B, Sq, H, Dh), 0, 2, 1, 3)
        scores = torch.einsum("bhqd,bhkd->bhqk", q, k_cache) * (Dh ** -0.5)
        p = _softmax(scores, axis=-1)
        o = torch.einsum("bhqk,bhkd->bhqd", p, v_cache)
        return (lambda x, *d: x.permute(*d))(o, 0, 2, 1, 3).reshape(B, Sq, H * Dh) @ wo

    def _B_ref(x, k_cache, v_cache, wq, wo):
        B, Sq, D = x.shape
        H, Dh = 32, 128
        q = (lambda x, *d: x.permute(*d))((x @ wq).reshape(B, Sq, H, Dh), 0, 2, 1, 3)
        scores = torch.einsum("bhqd,bhkd->bhqk", q, k_cache) * (Dh ** -0.5)
        p = _softmax(scores, axis=-1)
        o = torch.einsum("bhqk,bhkd->bhqd", p, v_cache)
        return (lambda x, *d: x.permute(*d))(o, 0, 2, 1, 3).reshape(B, Sq, H * Dh) @ wo

    a = _A_ref(A_x, A_k_cache, A_v_cache, A_wq, A_wo)
    b = _B_ref(B_x, B_k_cache, B_v_cache, B_wq, B_wo)
    return torch.concatenate([a, b], axis=-1)
```

```cpp
#include <cuda_runtime.h>
#include <cuda_bf16.h>
#include <cuda.h>
#include <stdint.h>

#define DEVINL __device__ __forceinline__

constexpr int STAGES = 4;
constexpr int A_BYTES = 16384;
constexpr int B_BYTES = 32768;
constexpr int STAGE_BYTES = A_BYTES + B_BYTES;
constexpr int SMEM_BYTES = STAGES * STAGE_BYTES + 1024 + 256;

struct Maps {
    CUtensorMap x[2];
    CUtensorMap wq[2];
    CUtensorMap k[2];
    CUtensorMap v[2];
    CUtensorMap wo[2];
    CUtensorMap o;
};

__device__ __nv_bfloat16 g_o[2 * 512 * 4096];
__device__ float g_part[128 * 128 * 256];
__device__ unsigned int g_oflag[128];
__device__ unsigned int g_ocons[128];
__device__ unsigned int g_rflag[32];
__device__ unsigned int g_rcons[32];

DEVINL uint32_t smem_u32(const void* p) { return (uint32_t)__cvta_generic_to_shared(p); }

DEVINL void mbar_init(uint32_t bar, uint32_t count) {
    asm volatile("mbarrier.init.shared::cta.b64 [%0], %1;" ::"r"(bar), "r"(count));
}
DEVINL void mbar_expect_tx(uint32_t bar, uint32_t bytes) {
    asm volatile("mbarrier.arrive.expect_tx.shared::cta.b64 _, [%0], %1;" ::"r"(bar), "r"(bytes) : "memory");
}
DEVINL void mbar_arrive(uint32_t bar) {
    asm volatile("mbarrier.arrive.shared::cta.b64 _, [%0];" ::"r"(bar) : "memory");
}
DEVINL void mbar_arrive_remote(uint32_t bar, uint32_t cta) {
    asm volatile(
        "{\n\t.reg .b32 ra;\n\t"
        "mapa.shared::cluster.u32 ra, %0, %1;\n\t"
        "mbarrier.arrive.release.cluster.shared::cluster.b64 _, [ra];\n\t}"
        ::"r"(bar), "r"(cta) : "memory");
}
DEVINL void mbar_wait(uint32_t bar, uint32_t parity) {
    asm volatile(
        "{\n\t.reg .pred p;\n\t"
        "WAIT_LOOP:\n\t"
        "mbarrier.try_wait.parity.shared::cta.b64 p, [%0], %1, 0x989680;\n\t"
        "@p bra DONE;\n\t"
        "bra WAIT_LOOP;\n\t"
        "DONE:\n\t}"
        ::"r"(bar), "r"(parity) : "memory");
}
DEVINL void mbar_wait_cluster(uint32_t bar, uint32_t parity) {
    asm volatile(
        "{\n\t.reg .pred p;\n\t"
        "WAIT_LOOP:\n\t"
        "mbarrier.try_wait.parity.acquire.cluster.shared::cta.b64 p, [%0], %1, 0x989680;\n\t"
        "@p bra DONE;\n\t"
        "bra WAIT_LOOP;\n\t"
        "DONE:\n\t}"
        ::"r"(bar), "r"(parity) : "memory");
}

DEVINL void tma_load_2d(uint32_t dst, const CUtensorMap* map, int c0, int c1, uint32_t bar) {
    asm volatile(
        "cp.async.bulk.tensor.2d.shared::cluster.global.mbarrier::complete_tx::bytes [%0], [%1, {%3, %4}], [%2];"
        ::"r"(dst), "l"(map), "r"(bar), "r"(c0), "r"(c1) : "memory");
}
DEVINL void tma_load_2d_mc(uint32_t dst, const CUtensorMap* map, int c0, int c1, uint32_t bar, uint16_t mask) {
    asm volatile(
        "cp.async.bulk.tensor.2d.shared::cluster.global.mbarrier::complete_tx::bytes.multicast::cluster [%0], [%1, {%3, %4}], [%2], %5;"
        ::"r"(dst), "l"(map), "r"(bar), "r"(c0), "r"(c1), "h"(mask) : "memory");
}
DEVINL void tma_store_2d(const CUtensorMap* map, uint32_t src, int c0, int c1) {
    asm volatile(
        "cp.async.bulk.tensor.2d.global.shared::cta.bulk_group [%0, {%2, %3}], [%1];"
        ::"l"(map), "r"(src), "r"(c0), "r"(c1) : "memory");
}
DEVINL void l2_prefetch(const void* p, uint32_t bytes) {
    asm volatile("cp.async.bulk.prefetch.L2.global [%0], %1;" ::"l"(p), "r"(bytes) : "memory");
}
DEVINL void fence_proxy_async() { asm volatile("fence.proxy.async;" ::: "memory"); }
DEVINL void fence_proxy_async_smem() { asm volatile("fence.proxy.async.shared::cta;" ::: "memory"); }

DEVINL void wgmma_fence() { asm volatile("wgmma.fence.sync.aligned;" ::: "memory"); }
DEVINL void wgmma_commit() { asm volatile("wgmma.commit_group.sync.aligned;" ::: "memory"); }
template <int N> DEVINL void wgmma_wait() { asm volatile("wgmma.wait_group.sync.aligned %0;" ::"n"(N) : "memory"); }

DEVINL uint64_t make_desc(uint32_t addr, uint32_t lbo_bytes, uint32_t sbo_bytes) {
    uint64_t d = 0;
    d |= (uint64_t)((addr & 0x3FFFF) >> 4);
    d |= (uint64_t)((lbo_bytes >> 4) & 0x3FFF) << 16;
    d |= (uint64_t)((sbo_bytes >> 4) & 0x3FFF) << 32;
    d |= (uint64_t)1 << 62;
    return d;
}

#define R8(a, i) "+f"(a[i]), "+f"(a[i + 1]), "+f"(a[i + 2]), "+f"(a[i + 3]), "+f"(a[i + 4]), "+f"(a[i + 5]), "+f"(a[i + 6]), "+f"(a[i + 7])
#define R32(a, i) R8(a, i), R8(a, i + 8), R8(a, i + 16), R8(a, i + 24)

DEVINL void wgmma_m64n256k16_ss(float (&d)[128], uint64_t da, uint64_t db) {
    asm volatile(
        "wgmma.mma_async.sync.aligned.m64n256k16.f32.bf16.bf16 "
        "{%0,%1,%2,%3,%4,%5,%6,%7,%8,%9,%10,%11,%12,%13,%14,%15,%16,%17,%18,%19,%20,%21,%22,%23,%24,%25,%26,%27,%28,%29,%30,%31,"
        "%32,%33,%34,%35,%36,%37,%38,%39,%40,%41,%42,%43,%44,%45,%46,%47,%48,%49,%50,%51,%52,%53,%54,%55,%56,%57,%58,%59,%60,%61,%62,%63,"
        "%64,%65,%66,%67,%68,%69,%70,%71,%72,%73,%74,%75,%76,%77,%78,%79,%80,%81,%82,%83,%84,%85,%86,%87,%88,%89,%90,%91,%92,%93,%94,%95,"
        "%96,%97,%98,%99,%100,%101,%102,%103,%104,%105,%106,%107,%108,%109,%110,%111,%112,%113,%114,%115,%116,%117,%118,%119,%120,%121,%122,%123,%124,%125,%126,%127},"
        " %128, %129, 1, 1, 1, 0, 1;"
        : R32(d, 0), R32(d, 32), R32(d, 64), R32(d, 96)
        : "l"(da), "l"(db));
}
DEVINL void wgmma_m64n64k16_rs(float (&d)[32], uint32_t a0, uint32_t a1, uint32_t a2, uint32_t a3, uint64_t db, int scale_d) {
    asm volatile(
        "{\n\t.reg .pred p;\n\tsetp.ne.b32 p, %37, 0;\n\t"
        "wgmma.mma_async.sync.aligned.m64n64k16.f32.bf16.bf16 "
        "{%0,%1,%2,%3,%4,%5,%6,%7,%8,%9,%10,%11,%12,%13,%14,%15,%16,%17,%18,%19,%20,%21,%22,%23,%24,%25,%26,%27,%28,%29,%30,%31},"
        " {%32,%33,%34,%35}, %36, p, 1, 1, 0;\n\t}"
        : R32(d, 0)
        : "r"(a0), "r"(a1), "r"(a2), "r"(a3), "l"(db), "r"(scale_d));
}
DEVINL void wgmma_m64n128k16_rs(float (&d)[64], uint32_t a0, uint32_t a1, uint32_t a2, uint32_t a3, uint64_t db, int scale_d) {
    asm volatile(
        "{\n\t.reg .pred p;\n\tsetp.ne.b32 p, %69, 0;\n\t"
        "wgmma.mma_async.sync.aligned.m64n128k16.f32.bf16.bf16 "
        "{%0,%1,%2,%3,%4,%5,%6,%7,%8,%9,%10,%11,%12,%13,%14,%15,%16,%17,%18,%19,%20,%21,%22,%23,%24,%25,%26,%27,%28,%29,%30,%31,"
        "%32,%33,%34,%35,%36,%37,%38,%39,%40,%41,%42,%43,%44,%45,%46,%47,%48,%49,%50,%51,%52,%53,%54,%55,%56,%57,%58,%59,%60,%61,%62,%63},"
        " {%64,%65,%66,%67}, %68, p, 1, 1, 1;\n\t}"
        : R32(d, 0), R32(d, 32)
        : "r"(a0), "r"(a1), "r"(a2), "r"(a3), "l"(db), "r"(scale_d));
}

DEVINL uint32_t pack_bf16(float lo, float hi) {
    __nv_bfloat162 t = __floats2bfloat162_rn(lo, hi);
    return *reinterpret_cast<uint32_t*>(&t);
}
DEVINL void stmatrix_x4(uint32_t addr, uint32_t r0, uint32_t r1, uint32_t r2, uint32_t r3) {
    asm volatile("stmatrix.sync.aligned.m8n8.x4.shared.b16 [%0], {%1,%2,%3,%4};" ::"r"(addr), "r"(r0), "r"(r1), "r"(r2), "r"(r3) : "memory");
}
DEVINL unsigned int ld_acquire(const unsigned int* p) {
    unsigned int v;
    asm volatile("ld.acquire.gpu.global.u32 %0, [%1];" : "=r"(v) : "l"(p) : "memory");
    return v;
}

__global__ void __cluster_dims__(2, 1, 1) __launch_bounds__(384, 1)
mha2_fused_kernel(const __grid_constant__ Maps maps,
                  const __nv_bfloat16* __restrict__ kA, const __nv_bfloat16* __restrict__ vA,
                  const __nv_bfloat16* __restrict__ kB, const __nv_bfloat16* __restrict__ vB,
                  __nv_bfloat16* __restrict__ out)
{
    extern __shared__ uint8_t smem_raw[];
    const uint32_t smem_base = (smem_u32(smem_raw) + 1023u) & ~1023u;
    const uint32_t bar_base = smem_base + STAGES * STAGE_BYTES;
    auto full_bar = [&](int s) { return bar_base + 8u * s; };
    auto empty_bar = [&](int s) { return bar_base + 64u + 8u * s; };

    const int tid = threadIdx.x;
    const int wg = tid >> 7;
    uint32_t rank;
    asm volatile("mov.u32 %0, %%cluster_ctarank;" : "=r"(rank));
    const int cl = blockIdx.x >> 1;
    const int blk = cl >> 5;
    const int mp = (cl >> 4) & 1;
    const int m = mp * 2 + (int)rank;
    const int hp = cl & 15;
    const int n2 = (cl >> 2) & 3;
    const int s2 = cl & 3;

    if (tid == 0) {
        for (int s = 0; s < STAGES; s++) {
            mbar_init(full_bar(s), 1);
            mbar_init(empty_bar(s), 4);
        }
        asm volatile("fence.mbarrier_init.release.cluster;" ::: "memory");
    }
    __syncthreads();
    asm volatile("barrier.cluster.arrive.release.aligned;\n\tbarrier.cluster.wait.acquire.aligned;" ::: "memory");

    if (wg == 0) {
        asm volatile("setmaxnreg.dec.sync.aligned.u32 40;");
        if (tid == 0) {
            int it = 0;
            auto acquire = [&](uint32_t bytes) {
                const int st = it % STAGES;
                mbar_wait_cluster(empty_bar(st), ((it / STAGES) & 1) ^ 1);
                mbar_expect_tx(full_bar(st), bytes);
                return st;
            };
            const __nv_bfloat16* kp = blk ? kB : kA;
            const __nv_bfloat16* vp = blk ? vB : vA;
            for (int kb = 0; kb < 16; kb++, it++) {
                const int st = acquire(STAGE_BYTES);
                const uint32_t sa = smem_base + st * STAGE_BYTES;
                tma_load_2d(sa, &maps.x[blk], kb * 64, m * 128, full_bar(st));
                const uint32_t sb = sa + A_BYTES + rank * 16384;
                tma_load_2d_mc(sb, &maps.wq[blk], hp * 256 + rank * 128, kb * 64, full_bar(st), 3);
                tma_load_2d_mc(sb + 8192, &maps.wq[blk], hp * 256 + rank * 128 + 64, kb * 64, full_bar(st), 3);
                if (kb >= 2 && kb < 10) {
                    const int j = kb - 2;
                    const int b = m * 4 + (j >> 1);
                    const __nv_bfloat16* p = ((j & 1) ? vp : kp) + ((size_t)(b * 32 + hp * 2)) * 4096;
                    l2_prefetch(p, 16384);
                }
            }
            for (int j = 0; j < 4; j++, it++) {
                const int st = acquire(32768);
                const uint32_t sk = smem_base + st * STAGE_BYTES;
                const int h = hp * 2 + (j >> 1);
                for (int bi = 0; bi < 2; bi++) {
                    const int b = m * 4 + (j & 1) * 2 + bi;
                    const int row = (b * 32 + h) * 32;
                    for (int dh = 0; dh < 2; dh++) {
                        tma_load_2d(sk + dh * 8192 + bi * 4096, &maps.k[blk], dh * 64, row, full_bar(st));
                        tma_load_2d(sk + 16384 + dh * 8192 + bi * 4096, &maps.v[blk], dh * 64, row, full_bar(st));
                    }
                }
            }
            const int it0 = it;
            for (int kb = 0; kb < 4; kb++, it++) {
                const int st = acquire(STAGE_BYTES);
                const uint32_t sb = smem_base + st * STAGE_BYTES + A_BYTES + rank * 16384;
                tma_load_2d_mc(sb, &maps.wo[blk], n2 * 256 + rank * 128, s2 * 1024 + kb * 64, full_bar(st), 3);
                tma_load_2d_mc(sb + 8192, &maps.wo[blk], n2 * 256 + rank * 128 + 64, s2 * 1024 + kb * 64, full_bar(st), 3);
            }
            for (int kb = 0; kb < 16; kb++) {
                if (kb >= 4) {
                    const int st = acquire(STAGE_BYTES);
                    const uint32_t sb = smem_base + st * STAGE_BYTES + A_BYTES + rank * 16384;
                    tma_load_2d_mc(sb, &maps.wo[blk], n2 * 256 + rank * 128, s2 * 1024 + kb * 64, full_bar(st), 3);
                    tma_load_2d_mc(sb + 8192, &maps.wo[blk], n2 * 256 + rank * 128 + 64, s2 * 1024 + kb * 64, full_bar(st), 3);
                    it++;
                }
                if ((kb & 3) == 0) {
                    const int fi = (blk * 4 + m) * 16 + s2 * 4 + (kb >> 2);
                    unsigned int spins = 0;
                    while (ld_acquire(&g_oflag[fi]) < 2u) {
                        if (++spins > (1u << 26)) __trap();
                    }
                    if (atomicAdd(&g_ocons[fi], 1u) == 3u) {
                        g_ocons[fi] = 0u;
                        g_oflag[fi] = 0u;
                    }
                    fence_proxy_async();
                }
                const int st = (it0 + kb) % STAGES;
                const uint32_t sa = smem_base + st * STAGE_BYTES;
                tma_load_2d(sa, &maps.o, s2 * 1024 + kb * 64, blk * 512 + m * 128, full_bar(st));
                tma_load_2d(sa + 8192, &maps.o, s2 * 1024 + kb * 64, blk * 512 + m * 128 + 64, full_bar(st));
            }
        }
    } else {
        asm volatile("setmaxnreg.inc.sync.aligned.u32 232;");
        const int w = wg - 1;
        const int wtid = tid & 127;
        const int warp = wtid >> 5, lane = tid & 31;
        int it = 0;
        auto release = [&](int st) {
            if (wtid == 0) {
                mbar_arrive(empty_bar(st));
                mbar_arrive_remote(empty_bar(st), rank ^ 1);
            }
        };
        auto mainloop = [&](float (&acc)[128]) {
#pragma unroll
            for (int i = 0; i < 128; i++) acc[i] = 0.f;
            for (int kb = 0; kb < 16; kb++, it++) {
                const int st = it % STAGES;
                mbar_wait(full_bar(st), (it / STAGES) & 1);
                const uint32_t sa = smem_base + st * STAGE_BYTES + w * 8192;
                const uint32_t sb = smem_base + st * STAGE_BYTES + A_BYTES;
                wgmma_fence();
#pragma unroll
                for (int k = 0; k < 4; k++) {
                    wgmma_m64n256k16_ss(acc, make_desc(sa + k * 32, 16, 1024), make_desc(sb + k * 2048, 8192, 1024));
                }
                wgmma_commit();
                if (kb > 0) {
                    wgmma_wait<1>();
                    release((it - 1) % STAGES);
                }
            }
            wgmma_wait<0>();
            release((it - 1) % STAGES);
        };

        float acc[128];
        mainloop(acc);

        uint32_t qf[64];
#pragma unroll
        for (int i = 0; i < 64; i++) qf[i] = pack_bf16(acc[2 * i], acc[2 * i + 1]);
#pragma unroll
        for (int j = 0; j < 4; j++, it++) {
            const int st = it % STAGES;
            mbar_wait(full_bar(st), (it / STAGES) & 1);
            if ((j & 1) == w) {
                const int hh = j >> 1;
                const uint32_t sk = smem_base + st * STAGE_BYTES;
                const uint32_t sv = sk + 16384;
                const uint32_t so = sk + 32768;
                float sc[32];
                wgmma_fence();
#pragma unroll
                for (int t = 0; t < 8; t++) {
                    const int g = hh * 16 + 2 * t;
                    wgmma_m64n64k16_rs(sc, qf[2 * g], qf[2 * g + 1], qf[2 * g + 2], qf[2 * g + 3],
                                       make_desc(sk + (t >> 2) * 8192 + (t & 3) * 32, 16, 1024), t > 0);
                }
                wgmma_commit();
                wgmma_wait<0>();
                const bool hi = warp >= 2;
                float v0[8], v1[8];
#pragma unroll
                for (int g = 0; g < 4; g++) {
                    v0[2 * g] = hi ? sc[(g + 4) * 4 + 0] : sc[g * 4 + 0];
                    v0[2 * g + 1] = hi ? sc[(g + 4) * 4 + 1] : sc[g * 4 + 1];
                    v1[2 * g] = hi ? sc[(g + 4) * 4 + 2] : sc[g * 4 + 2];
                    v1[2 * g + 1] = hi ? sc[(g + 4) * 4 + 3] : sc[g * 4 + 3];
                }
                float m0 = v0[0], m1 = v1[0];
#pragma unroll
                for (int i = 1; i < 8; i++) { m0 = fmaxf(m0, v0[i]); m1 = fmaxf(m1, v1[i]); }
                m0 = fmaxf(m0, __shfl_xor_sync(0xffffffffu, m0, 1));
                m0 = fmaxf(m0, __shfl_xor_sync(0xffffffffu, m0, 2));
                m1 = fmaxf(m1, __shfl_xor_sync(0xffffffffu, m1, 1));
                m1 = fmaxf(m1, __shfl_xor_sync(0xffffffffu, m1, 2));
                const float cs = 0.08838834764831845f * 1.4426950408889634f;
                float s0 = 0.f, s1 = 0.f;
#pragma unroll
                for (int i = 0; i < 8; i++) {
                    v0[i] = exp2f((v0[i] - m0) * cs); s0 += v0[i];
                    v1[i] = exp2f((v1[i] - m1) * cs); s1 += v1[i];
                }
                s0 += __shfl_xor_sync(0xffffffffu, s0, 1);
                s0 += __shfl_xor_sync(0xffffffffu, s0, 2);
                s1 += __shfl_xor_sync(0xffffffffu, s1, 1);
                s1 += __shfl_xor_sync(0xffffffffu, s1, 2);
                const float i0 = 1.f / s0, i1 = 1.f / s1;
                uint32_t pf[8];
#pragma unroll
                for (int t = 0; t < 2; t++) {
                    pf[4 * t + 0] = pack_bf16(v0[4 * t + 0] * i0, v0[4 * t + 1] * i0);
                    pf[4 * t + 1] = pack_bf16(v1[4 * t + 0] * i1, v1[4 * t + 1] * i1);
                    pf[4 * t + 2] = pack_bf16(v0[4 * t + 2] * i0, v0[4 * t + 3] * i0);
                    pf[4 * t + 3] = pack_bf16(v1[4 * t + 2] * i1, v1[4 * t + 3] * i1);
                }
                float oc[64];
                wgmma_fence();
#pragma unroll
                for (int t = 0; t < 4; t++) {
                    const bool val = (t >> 1) == (hi ? 1 : 0);
                    const int tt = t & 1;
                    wgmma_m64n128k16_rs(oc, val ? pf[4 * tt + 0] : 0u, val ? pf[4 * tt + 1] : 0u, val ? pf[4 * tt + 2] : 0u, val ? pf[4 * tt + 3] : 0u,
                                        make_desc(sv + t * 2048, 8192, 1024), t > 0);
                }
                wgmma_commit();
                wgmma_wait<0>();
#pragma unroll
                for (int c = 0; c < 8; c++) {
                    const uint32_t r0 = pack_bf16(oc[8 * c + 0], oc[8 * c + 1]);
                    const uint32_t r1 = pack_bf16(oc[8 * c + 2], oc[8 * c + 3]);
                    const uint32_t r2 = pack_bf16(oc[8 * c + 4], oc[8 * c + 5]);
                    const uint32_t r3 = pack_bf16(oc[8 * c + 6], oc[8 * c + 7]);
                    const int row = warp * 16 + (lane & 7) + ((lane >> 3) & 1) * 8;
                    const int chunk = (c & 3) * 2 + (lane >> 4);
                    const uint32_t addr = so + (c >> 2) * 8192 + row * 128 + ((chunk ^ (row & 7)) << 4);
                    stmatrix_x4(addr, r0, r1, r2, r3);
                }
                fence_proxy_async_smem();
                asm volatile("bar.sync %0, 128;" ::"r"(1 + w) : "memory");
                if (wtid == 0) {
                    const int col = (hp * 2 + hh) * 128;
                    const int row = blk * 512 + m * 128 + w * 64;
                    tma_store_2d(&maps.o, so, col, row);
                    tma_store_2d(&maps.o, so + 8192, col + 64, row);
                    asm volatile("cp.async.bulk.commit_group;" ::: "memory");
                    asm volatile("cp.async.bulk.wait_group 0;" ::: "memory");
                    if (hh == 1) {
                        __threadfence();
                        atomicAdd(&g_oflag[(blk * 4 + m) * 16 + hp], 1u);
                    }
                }
            }
            release(st);
        }

        mainloop(acc);

        {
            const int tile = (blk * 4 + m) * 4 + n2;
            float* base = g_part + (size_t)(tile * 4) * (128 * 256);
#pragma unroll
            for (int q = 0; q < 4; q++) {
                if (q != s2) {
                    float4* p = reinterpret_cast<float4*>(base + (size_t)s2 * (128 * 256)) + ((q * 2 + w) * 8) * 128 + wtid;
#pragma unroll
                    for (int i = 0; i < 8; i++)
                        p[i * 128] = make_float4(acc[q * 32 + 4 * i], acc[q * 32 + 4 * i + 1], acc[q * 32 + 4 * i + 2], acc[q * 32 + 4 * i + 3]);
                }
            }
            __threadfence();
            asm volatile("bar.sync 3, 256;" ::: "memory");
            if (w == 0 && wtid == 0) {
                atomicAdd(&g_rflag[tile], 1u);
                unsigned int spins = 0;
                while (ld_acquire(&g_rflag[tile]) < 4u) {
                    if (++spins > (1u << 26)) __trap();
                }
                if (atomicAdd(&g_rcons[tile], 1u) == 3u) {
                    g_rcons[tile] = 0u;
                    g_rflag[tile] = 0u;
                }
            }
            asm volatile("bar.sync 3, 256;" ::: "memory");
            float r[32];
#pragma unroll
            for (int q = 0; q < 4; q++) {
                if (q == s2) {
#pragma unroll
                    for (int i = 0; i < 32; i++) r[i] = acc[q * 32 + i];
                }
            }
#pragma unroll
            for (int sp = 0; sp < 4; sp++) {
                if (sp != s2) {
                    const float4* p = reinterpret_cast<const float4*>(base + (size_t)sp * (128 * 256)) + ((s2 * 2 + w) * 8) * 128 + wtid;
#pragma unroll
                    for (int i = 0; i < 8; i++) {
                        const float4 t = __ldcg(p + i * 128);
                        r[4 * i] += t.x; r[4 * i + 1] += t.y; r[4 * i + 2] += t.z; r[4 * i + 3] += t.w;
                    }
                }
            }
            const int row = m * 128 + w * 64 + warp * 16 + (lane >> 2);
            __nv_bfloat16* op = out + (size_t)row * 2048 + blk * 1024 + n2 * 256 + s2 * 64 + (lane & 3) * 2;
#pragma unroll
            for (int g = 0; g < 8; g++) {
                *reinterpret_cast<uint32_t*>(op + g * 8) = pack_bf16(r[4 * g], r[4 * g + 1]);
                *reinterpret_cast<uint32_t*>(op + 8 * 2048 + g * 8) = pack_bf16(r[4 * g + 2], r[4 * g + 3]);
            }
        }
    }
    __syncwarp();
    asm volatile("barrier.cluster.arrive.release.aligned;\n\tbarrier.cluster.wait.acquire.aligned;" ::: "memory");
}

typedef CUresult (*EncodeFn)(CUtensorMap*, CUtensorMapDataType, cuuint32_t, void*, const cuuint64_t*, const cuuint64_t*,
                             const cuuint32_t*, const cuuint32_t*, CUtensorMapInterleave, CUtensorMapSwizzle,
                             CUtensorMapL2promotion, CUtensorMapFloatOOBfill);

static void make_map(EncodeFn fn, CUtensorMap* map, const void* ptr, uint64_t rows, uint64_t cols, uint32_t box_rows) {
    cuuint64_t dims[2] = {cols, rows};
    cuuint64_t strides[1] = {cols * 2};
    cuuint32_t box[2] = {64, box_rows};
    cuuint32_t estr[2] = {1, 1};
    fn(map, CU_TENSOR_MAP_DATA_TYPE_BFLOAT16, 2, const_cast<void*>(ptr), dims, strides, box, estr,
       CU_TENSOR_MAP_INTERLEAVE_NONE, CU_TENSOR_MAP_SWIZZLE_128B, CU_TENSOR_MAP_L2_PROMOTION_L2_128B, CU_TENSOR_MAP_FLOAT_OOB_FILL_NONE);
}

extern "C" void kernel_launch(void* const* d_in, const int* in_sizes, int n_in, void* d_out, int out_size) {
    static Maps maps;
    static bool ready = false;
    static void* cached[11];
    bool same = ready;
    for (int i = 0; i < 10 && same; i++) same = (cached[i] == d_in[i]);
    if (!same) {
        void* fnp = nullptr;
        cudaDriverEntryPointQueryResult qres;
        cudaGetDriverEntryPoint("cuTensorMapEncodeTiled", &fnp, cudaEnableDefault, &qres);
        EncodeFn fn = (EncodeFn)fnp;
        void* optr = nullptr;
        cudaGetSymbolAddress(&optr, g_o);
        for (int b = 0; b < 2; b++) {
            make_map(fn, &maps.x[b], d_in[5 * b + 0], 512, 1024, 128);
            make_map(fn, &maps.k[b], d_in[5 * b + 1], 16384, 128, 32);
            make_map(fn, &maps.v[b], d_in[5 * b + 2], 16384, 128, 32);
            make_map(fn, &maps.wq[b], d_in[5 * b + 3], 1024, 4096, 64);
            make_map(fn, &maps.wo[b], d_in[5 * b + 4], 4096, 1024, 64);
        }
        make_map(fn, &maps.o, optr, 1024, 4096, 64);
        cudaFuncSetAttribute(mha2_fused_kernel, cudaFuncAttributeMaxDynamicSharedMemorySize, SMEM_BYTES);
        for (int i = 0; i < 10; i++) cached[i] = d_in[i];
        ready = true;
    }
    mha2_fused_kernel<<<128, 384, SMEM_BYTES>>>(maps,
        (const __nv_bfloat16*)d_in[1], (const __nv_bfloat16*)d_in[2],
        (const __nv_bfloat16*)d_in[6], (const __nv_bfloat16*)d_in[7],
        (__nv_bfloat16*)d_out);
}
```

```cpp
#include <cuda_runtime.h>
#include <cuda_bf16.h>
#include <cuda.h>
#include <stdint.h>

#define DEVINL __device__ __forceinline__

constexpr int STAGES = 4;
constexpr int A_BYTES = 16384;
constexpr int B_BYTES = 32768;
constexpr int STAGE_BYTES = A_BYTES + B_BYTES;
constexpr int SMEM_BYTES = STAGES * STAGE_BYTES + 1024 + 256;

struct Maps {
    CUtensorMap x[2];
    CUtensorMap wq[2];
    CUtensorMap k[2];
    CUtensorMap v[2];
    CUtensorMap wo[2];
    CUtensorMap o;
};

__device__ __nv_bfloat16 g_o[2 * 512 * 4096];
__device__ float g_part[128 * 128 * 256];
__device__ unsigned int g_oflag[128];
__device__ unsigned int g_ocons[128];
__device__ unsigned int g_rflag[32];
__device__ unsigned int g_rcons[32];

#define TL(i)
DEVINL uint32_t smem_u32(const void* p) { return (uint32_t)__cvta_generic_to_shared(p); }

DEVINL void mbar_init(uint32_t bar, uint32_t count) {
    asm volatile("mbarrier.init.shared::cta.b64 [%0], %1;" ::"r"(bar), "r"(count));
}
DEVINL void mbar_expect_tx(uint32_t bar, uint32_t bytes) {
    asm volatile("mbarrier.arrive.expect_tx.shared::cta.b64 _, [%0], %1;" ::"r"(bar), "r"(bytes) : "memory");
}
DEVINL void mbar_arrive(uint32_t bar) {
    asm volatile("mbarrier.arrive.shared::cta.b64 _, [%0];" ::"r"(bar) : "memory");
}
DEVINL void mbar_arrive_remote(uint32_t bar, uint32_t cta) {
    asm volatile(
        "{\n\t.reg .b32 ra;\n\t"
        "mapa.shared::cluster.u32 ra, %0, %1;\n\t"
        "mbarrier.arrive.shared::cluster.b64 _, [ra];\n\t}"
        ::"r"(bar), "r"(cta) : "memory");
}
DEVINL void mbar_wait(uint32_t bar, uint32_t parity) {
    asm volatile(
        "{\n\t.reg .pred p;\n\t"
        "WAIT_LOOP:\n\t"
        "mbarrier.try_wait.parity.shared::cta.b64 p, [%0], %1, 0x989680;\n\t"
        "@p bra DONE;\n\t"
        "bra WAIT_LOOP;\n\t"
        "DONE:\n\t}"
        ::"r"(bar), "r"(parity) : "memory");
}
DEVINL void mbar_wait_cluster(uint32_t bar, uint32_t parity) {
    asm volatile(
        "{\n\t.reg .pred p;\n\t"
        "WAIT_LOOP:\n\t"
        "mbarrier.try_wait.parity.shared::cta.b64 p, [%0], %1, 0x989680;\n\t"
        "@p bra DONE;\n\t"
        "bra WAIT_LOOP;\n\t"
        "DONE:\n\t}"
        ::"r"(bar), "r"(parity) : "memory");
}

DEVINL void tma_load_2d(uint32_t dst, const CUtensorMap* map, int c0, int c1, uint32_t bar) {
    asm volatile(
        "cp.async.bulk.tensor.2d.shared::cluster.global.mbarrier::complete_tx::bytes [%0], [%1, {%3, %4}], [%2];"
        ::"r"(dst), "l"(map), "r"(bar), "r"(c0), "r"(c1) : "memory");
}
DEVINL void tma_load_2d_mc(uint32_t dst, const CUtensorMap* map, int c0, int c1, uint32_t bar, uint16_t mask) {
    asm volatile(
        "cp.async.bulk.tensor.2d.shared::cluster.global.mbarrier::complete_tx::bytes.multicast::cluster [%0], [%1, {%3, %4}], [%2], %5;"
        ::"r"(dst), "l"(map), "r"(bar), "r"(c0), "r"(c1), "h"(mask) : "memory");
}
DEVINL void tma_store_2d(const CUtensorMap* map, uint32_t src, int c0, int c1) {
    asm volatile(
        "cp.async.bulk.tensor.2d.global.shared::cta.bulk_group [%0, {%2, %3}], [%1];"
        ::"l"(map), "r"(src), "r"(c0), "r"(c1) : "memory");
}
DEVINL void l2_prefetch(const void* p, uint32_t bytes) {
    asm volatile("cp.async.bulk.prefetch.L2.global [%0], %1;" ::"l"(p), "r"(bytes) : "memory");
}
DEVINL void fence_proxy_async() { asm volatile("fence.proxy.async;" ::: "memory"); }
DEVINL void fence_proxy_async_smem() { asm volatile("fence.proxy.async.shared::cta;" ::: "memory"); }

DEVINL void wgmma_fence() { asm volatile("wgmma.fence.sync.aligned;" ::: "memory"); }
DEVINL void wgmma_commit() { asm volatile("wgmma.commit_group.sync.aligned;" ::: "memory"); }
template <int N> DEVINL void wgmma_wait() { asm volatile("wgmma.wait_group.sync.aligned %0;" ::"n"(N) : "memory"); }

DEVINL uint64_t make_desc(uint32_t addr, uint32_t lbo_bytes, uint32_t sbo_bytes) {
    uint64_t d = 0;
    d |= (uint64_t)((addr & 0x3FFFF) >> 4);
    d |= (uint64_t)((lbo_bytes >> 4) & 0x3FFF) << 16;
    d |= (uint64_t)((sbo_bytes >> 4) & 0x3FFF) << 32;
    d |= (uint64_t)1 << 62;
    return d;
}

#define R8(a, i) "+f"(a[i]), "+f"(a[i + 1]), "+f"(a[i + 2]), "+f"(a[i + 3]), "+f"(a[i + 4]), "+f"(a[i + 5]), "+f"(a[i + 6]), "+f"(a[i + 7])
#define R32(a, i) R8(a, i), R8(a, i + 8), R8(a, i + 16), R8(a, i + 24)

DEVINL void wgmma_m64n256k16_ss(float (&d)[128], uint64_t da, uint64_t db) {
    asm volatile(
        "wgmma.mma_async.sync.aligned.m64n256k16.f32.bf16.bf16 "
        "{%0,%1,%2,%3,%4,%5,%6,%7,%8,%9,%10,%11,%12,%13,%14,%15,%16,%17,%18,%19,%20,%21,%22,%23,%24,%25,%26,%27,%28,%29,%30,%31,"
        "%32,%33,%34,%35,%36,%37,%38,%39,%40,%41,%42,%43,%44,%45,%46,%47,%48,%49,%50,%51,%52,%53,%54,%55,%56,%57,%58,%59,%60,%61,%62,%63,"
        "%64,%65,%66,%67,%68,%69,%70,%71,%72,%73,%74,%75,%76,%77,%78,%79,%80,%81,%82,%83,%84,%85,%86,%87,%88,%89,%90,%91,%92,%93,%94,%95,"
        "%96,%97,%98,%99,%100,%101,%102,%103,%104,%105,%106,%107,%108,%109,%110,%111,%112,%113,%114,%115,%116,%117,%118,%119,%120,%121,%122,%123,%124,%125,%126,%127},"
        " %128, %129, 1, 1, 1, 0, 1;"
        : R32(d, 0), R32(d, 32), R32(d, 64), R32(d, 96)
        : "l"(da), "l"(db));
}
DEVINL void wgmma_m64n64k16_rs(float (&d)[32], uint32_t a0, uint32_t a1, uint32_t a2, uint32_t a3, uint64_t db, int scale_d) {
    asm volatile(
        "{\n\t.reg .pred p;\n\tsetp.ne.b32 p, %37, 0;\n\t"
        "wgmma.mma_async.sync.aligned.m64n64k16.f32.bf16.bf16 "
        "{%0,%1,%2,%3,%4,%5,%6,%7,%8,%9,%10,%11,%12,%13,%14,%15,%16,%17,%18,%19,%20,%21,%22,%23,%24,%25,%26,%27,%28,%29,%30,%31},"
        " {%32,%33,%34,%35}, %36, p, 1, 1, 0;\n\t}"
        : R32(d, 0)
        : "r"(a0), "r"(a1), "r"(a2), "r"(a3), "l"(db), "r"(scale_d));
}
DEVINL void wgmma_m64n128k16_rs(float (&d)[64], uint32_t a0, uint32_t a1, uint32_t a2, uint32_t a3, uint64_t db, int scale_d) {
    asm volatile(
        "{\n\t.reg .pred p;\n\tsetp.ne.b32 p, %69, 0;\n\t"
        "wgmma.mma_async.sync.aligned.m64n128k16.f32.bf16.bf16 "
        "{%0,%1,%2,%3,%4,%5,%6,%7,%8,%9,%10,%11,%12,%13,%14,%15,%16,%17,%18,%19,%20,%21,%22,%23,%24,%25,%26,%27,%28,%29,%30,%31,"
        "%32,%33,%34,%35,%36,%37,%38,%39,%40,%41,%42,%43,%44,%45,%46,%47,%48,%49,%50,%51,%52,%53,%54,%55,%56,%57,%58,%59,%60,%61,%62,%63},"
        " {%64,%65,%66,%67}, %68, p, 1, 1, 1;\n\t}"
        : R32(d, 0), R32(d, 32)
        : "r"(a0), "r"(a1), "r"(a2), "r"(a3), "l"(db), "r"(scale_d));
}

DEVINL uint32_t pack_bf16(float lo, float hi) {
    __nv_bfloat162 t = __floats2bfloat162_rn(lo, hi);
    return *reinterpret_cast<uint32_t*>(&t);
}
DEVINL void stmatrix_x4(uint32_t addr, uint32_t r0, uint32_t r1, uint32_t r2, uint32_t r3) {
    asm volatile("stmatrix.sync.aligned.m8n8.x4.shared.b16 [%0], {%1,%2,%3,%4};" ::"r"(addr), "r"(r0), "r"(r1), "r"(r2), "r"(r3) : "memory");
}
DEVINL unsigned int ld_acquire(const unsigned int* p) {
    unsigned int v;
    asm volatile("ld.acquire.gpu.global.u32 %0, [%1];" : "=r"(v) : "l"(p) : "memory");
    return v;
}

__global__ void __cluster_dims__(2, 1, 1) __launch_bounds__(384, 1)
mha2_fused_kernel(const __grid_constant__ Maps maps,
                  const __nv_bfloat16* __restrict__ kA, const __nv_bfloat16* __restrict__ vA,
                  const __nv_bfloat16* __restrict__ kB, const __nv_bfloat16* __restrict__ vB,
                  __nv_bfloat16* __restrict__ out)
{
    extern __shared__ uint8_t smem_raw[];
    const uint32_t smem_base = (smem_u32(smem_raw) + 1023u) & ~1023u;
    const uint32_t bar_base = smem_base + STAGES * STAGE_BYTES;
    auto full_bar = [&](int s) { return bar_base + 8u * s; };
    auto empty_bar = [&](int s) { return bar_base + 64u + 8u * s; };

    const int tid = threadIdx.x;
    const int wg = tid >> 7;
    uint32_t rank;
    asm volatile("mov.u32 %0, %%cluster_ctarank;" : "=r"(rank));
    const int cl = blockIdx.x >> 1;
    const int blk = cl >> 5;
    const int mp = (cl >> 4) & 1;
    const int m = mp * 2 + (int)rank;
    const int hp = cl & 15;
    const int n2 = (cl >> 2) & 3;
    const int s2 = cl & 3;

    if (tid == 0) {
        for (int s = 0; s < STAGES; s++) {
            mbar_init(full_bar(s), 1);
            mbar_init(empty_bar(s), 4);
        }
        asm volatile("fence.mbarrier_init.release.cluster;" ::: "memory");
    }
    __syncthreads();
    asm volatile("barrier.cluster.arrive.release.aligned;\n\tbarrier.cluster.wait.acquire.aligned;" ::: "memory");

    TL(0);
    if (wg == 2) {
        asm volatile("setmaxnreg.dec.sync.aligned.u32 40;");
        if (tid == 256) {
            int it = 0;
            auto acquire = [&](uint32_t bytes) {
                const int st = it % STAGES;
                mbar_wait_cluster(empty_bar(st), ((it / STAGES) & 1) ^ 1);
                mbar_expect_tx(full_bar(st), bytes);
                return st;
            };
            const __nv_bfloat16* kp = blk ? kB : kA;
            const __nv_bfloat16* vp = blk ? vB : vA;
            for (int kb = 0; kb < 16; kb++, it++) {
                const int st = acquire(STAGE_BYTES);
                const uint32_t sa = smem_base + st * STAGE_BYTES;
                tma_load_2d(sa, &maps.x[blk], kb * 64, m * 128, full_bar(st));
                const uint32_t sb = sa + A_BYTES + rank * 16384;
                tma_load_2d_mc(sb, &maps.wq[blk], hp * 256 + rank * 128, kb * 64, full_bar(st), 3);
                tma_load_2d_mc(sb + 8192, &maps.wq[blk], hp * 256 + rank * 128 + 64, kb * 64, full_bar(st), 3);
                if (kb >= 2 && kb < 10) {
                    const int j = kb - 2;
                    const int b = m * 4 + (j >> 1);
                    const __nv_bfloat16* p = ((j & 1) ? vp : kp) + ((size_t)(b * 32 + hp * 2)) * 4096;
                    l2_prefetch(p, 16384);
                }
            }
            TL(1);
            for (int j = 0; j < 4; j++, it++) {
                const int st = acquire(32768);
                const uint32_t sk = smem_base + st * STAGE_BYTES;
                const int h = hp * 2 + (j >> 1);
                for (int bi = 0; bi < 2; bi++) {
                    const int b = m * 4 + (j & 1) * 2 + bi;
                    const int row = (b * 32 + h) * 32;
                    for (int dh = 0; dh < 2; dh++) {
                        tma_load_2d(sk + dh * 8192 + bi * 4096, &maps.k[blk], dh * 64, row, full_bar(st));
                        tma_load_2d(sk + 16384 + dh * 8192 + bi * 4096, &maps.v[blk], dh * 64, row, full_bar(st));
                    }
                }
            }
            TL(2);
            const int it0 = it;
            for (int kb = 0; kb < 4; kb++, it++) {
                const int st = acquire(STAGE_BYTES);
                const uint32_t sb = smem_base + st * STAGE_BYTES + A_BYTES + rank * 16384;
                tma_load_2d_mc(sb, &maps.wo[blk], n2 * 256 + rank * 128, s2 * 1024 + kb * 64, full_bar(st), 3);
                tma_load_2d_mc(sb + 8192, &maps.wo[blk], n2 * 256 + rank * 128 + 64, s2 * 1024 + kb * 64, full_bar(st), 3);
            }
            TL(3);
            for (int kb = 0; kb < 16; kb++) {
                if (kb == 1) TL(4);
                if (kb == 5) TL(5);
                if (kb == 9) TL(6);
                if (kb == 13) TL(7);
                if (kb >= 4) {
                    const int st = acquire(STAGE_BYTES);
                    const uint32_t sb = smem_base + st * STAGE_BYTES + A_BYTES + rank * 16384;
                    tma_load_2d_mc(sb, &maps.wo[blk], n2 * 256 + rank * 128, s2 * 1024 + kb * 64, full_bar(st), 3);
                    tma_load_2d_mc(sb + 8192, &maps.wo[blk], n2 * 256 + rank * 128 + 64, s2 * 1024 + kb * 64, full_bar(st), 3);
                    it++;
                }
                if ((kb & 3) == 0) {
                    const int fi = (blk * 4 + m) * 16 + s2 * 4 + (kb >> 2);
                    unsigned int spins = 0;
                    while (ld_acquire(&g_oflag[fi]) < 2u) {
                        if (++spins > (1u << 26)) break;
                    }
                    if (atomicAdd(&g_ocons[fi], 1u) == 3u) {
                        g_ocons[fi] = 0u;
                        g_oflag[fi] = 0u;
                    }
                    fence_proxy_async();
                }
                const int st = (it0 + kb) % STAGES;
                const uint32_t sa = smem_base + st * STAGE_BYTES;
                tma_load_2d(sa, &maps.o, s2 * 1024 + kb * 64, blk * 512 + m * 128, full_bar(st));
                tma_load_2d(sa + 8192, &maps.o, s2 * 1024 + kb * 64, blk * 512 + m * 128 + 64, full_bar(st));
            }
        }
        __syncwarp();
        TL(9);
        asm volatile("barrier.cluster.arrive.release.aligned;\n\tbarrier.cluster.wait.acquire.aligned;" ::: "memory");
    } else {
        asm volatile("setmaxnreg.inc.sync.aligned.u32 232;");
        const int w = wg;
        const int wtid = tid & 127;
        const int warp = wtid >> 5, lane = tid & 31;
        int it = 0;
        auto release = [&](int st) {
            if (wtid == 0) {
                mbar_arrive(empty_bar(st));
                mbar_arrive_remote(empty_bar(st), rank ^ 1);
            }
        };
        auto mainloop = [&](float (&acc)[128]) {
#pragma unroll
            for (int i = 0; i < 128; i++) acc[i] = 0.f;
            for (int kb = 0; kb < 16; kb++, it++) {
                const int st = it % STAGES;
                mbar_wait(full_bar(st), (it / STAGES) & 1);
                const uint32_t sa = smem_base + st * STAGE_BYTES + w * 8192;
                const uint32_t sb = smem_base + st * STAGE_BYTES + A_BYTES;
                wgmma_fence();
#pragma unroll
                for (int k = 0; k < 4; k++) {
                    wgmma_m64n256k16_ss(acc, make_desc(sa + k * 32, 16, 1024), make_desc(sb + k * 2048, 8192, 1024));
                }
                wgmma_commit();
                if (kb > 0) {
                    wgmma_wait<1>();
                    release((it - 1) % STAGES);
                }
            }
            wgmma_wait<0>();
            release((it - 1) % STAGES);
        };

        float acc[128];
        mainloop(acc);
        TL(1);

        uint32_t qf[64];
#pragma unroll
        for (int i = 0; i < 64; i++) qf[i] = pack_bf16(acc[2 * i], acc[2 * i + 1]);
#pragma unroll
        for (int j = 0; j < 4; j++, it++) {
            const int st = it % STAGES;
            mbar_wait(full_bar(st), (it / STAGES) & 1);
            if ((j & 1) == w) {
                const int hh = j >> 1;
                const uint32_t sk = smem_base + st * STAGE_BYTES;
                const uint32_t sv = sk + 16384;
                const uint32_t so = sk + 32768;
                float sc[32];
                wgmma_fence();
#pragma unroll
                for (int t = 0; t < 8; t++) {
                    const int g = hh * 16 + 2 * t;
                    wgmma_m64n64k16_rs(sc, qf[2 * g], qf[2 * g + 1], qf[2 * g + 2], qf[2 * g + 3],
                                       make_desc(sk + (t >> 2) * 8192 + (t & 3) * 32, 16, 1024), t > 0);
                }
                wgmma_commit();
                wgmma_wait<0>();
                const bool hi = warp >= 2;
                float v0[8], v1[8];
#pragma unroll
                for (int g = 0; g < 4; g++) {
                    v0[2 * g] = hi ? sc[(g + 4) * 4 + 0] : sc[g * 4 + 0];
                    v0[2 * g + 1] = hi ? sc[(g + 4) * 4 + 1] : sc[g * 4 + 1];
                    v1[2 * g] = hi ? sc[(g + 4) * 4 + 2] : sc[g * 4 + 2];
                    v1[2 * g + 1] = hi ? sc[(g + 4) * 4 + 3] : sc[g * 4 + 3];
                }
                float m0 = v0[0], m1 = v1[0];
#pragma unroll
                for (int i = 1; i < 8; i++) { m0 = fmaxf(m0, v0[i]); m1 = fmaxf(m1, v1[i]); }
                m0 = fmaxf(m0, __shfl_xor_sync(0xffffffffu, m0, 1));
                m0 = fmaxf(m0, __shfl_xor_sync(0xffffffffu, m0, 2));
                m1 = fmaxf(m1, __shfl_xor_sync(0xffffffffu, m1, 1));
                m1 = fmaxf(m1, __shfl_xor_sync(0xffffffffu, m1, 2));
                const float cs = 0.08838834764831845f * 1.4426950408889634f;
                float s0 = 0.f, s1 = 0.f;
#pragma unroll
                for (int i = 0; i < 8; i++) {
                    v0[i] = exp2f((v0[i] - m0) * cs); s0 += v0[i];
                    v1[i] = exp2f((v1[i] - m1) * cs); s1 += v1[i];
                }
                s0 += __shfl_xor_sync(0xffffffffu, s0, 1);
                s0 += __shfl_xor_sync(0xffffffffu, s0, 2);
                s1 += __shfl_xor_sync(0xffffffffu, s1, 1);
                s1 += __shfl_xor_sync(0xffffffffu, s1, 2);
                const float i0 = 1.f / s0, i1 = 1.f / s1;
                uint32_t pf[8];
#pragma unroll
                for (int t = 0; t < 2; t++) {
                    pf[4 * t + 0] = pack_bf16(v0[4 * t + 0] * i0, v0[4 * t + 1] * i0);
                    pf[4 * t + 1] = pack_bf16(v1[4 * t + 0] * i1, v1[4 * t + 1] * i1);
                    pf[4 * t + 2] = pack_bf16(v0[4 * t + 2] * i0, v0[4 * t + 3] * i0);
                    pf[4 * t + 3] = pack_bf16(v1[4 * t + 2] * i1, v1[4 * t + 3] * i1);
                }
                float oc[64];
                wgmma_fence();
#pragma unroll
                for (int t = 0; t < 4; t++) {
                    const bool val = (t >> 1) == (hi ? 1 : 0);
                    const int tt = t & 1;
                    wgmma_m64n128k16_rs(oc, val ? pf[4 * tt + 0] : 0u, val ? pf[4 * tt + 1] : 0u, val ? pf[4 * tt + 2] : 0u, val ? pf[4 * tt + 3] : 0u,
                                        make_desc(sv + t * 2048, 8192, 1024), t > 0);
                }
                wgmma_commit();
                wgmma_wait<0>();
#pragma unroll
                for (int c = 0; c < 8; c++) {
                    const uint32_t r0 = pack_bf16(oc[8 * c + 0], oc[8 * c + 1]);
                    const uint32_t r1 = pack_bf16(oc[8 * c + 2], oc[8 * c + 3]);
                    const uint32_t r2 = pack_bf16(oc[8 * c + 4], oc[8 * c + 5]);
                    const uint32_t r3 = pack_bf16(oc[8 * c + 6], oc[8 * c + 7]);
                    const int row = warp * 16 + (lane & 7) + ((lane >> 3) & 1) * 8;
                    const int chunk = (c & 3) * 2 + (lane >> 4);
                    const uint32_t addr = so + (c >> 2) * 8192 + row * 128 + ((chunk ^ (row & 7)) << 4);
                    stmatrix_x4(addr, r0, r1, r2, r3);
                }
                fence_proxy_async_smem();
                asm volatile("bar.sync %0, 128;" ::"r"(1 + w) : "memory");
                if (wtid == 0) {
                    const int col = (hp * 2 + hh) * 128;
                    const int row = blk * 512 + m * 128 + w * 64;
                    tma_store_2d(&maps.o, so, col, row);
                    tma_store_2d(&maps.o, so + 8192, col + 64, row);
                    asm volatile("cp.async.bulk.commit_group;" ::: "memory");
                    asm volatile("cp.async.bulk.wait_group 0;" ::: "memory");
                    if (hh == 1) {
                        __threadfence();
                        atomicAdd(&g_oflag[(blk * 4 + m) * 16 + hp], 1u);
                    }
                }
            }
            release(st);
            TL(2 + j);
        }

        mainloop(acc);
        TL(6);

        {
            const int tile = (blk * 4 + m) * 4 + n2;
            float* base = g_part + (size_t)(tile * 4) * (128 * 256);
#pragma unroll
            for (int q = 0; q < 4; q++) {
                if (q != s2) {
                    float4* p = reinterpret_cast<float4*>(base + (size_t)s2 * (128 * 256)) + ((q * 2 + w) * 8) * 128 + wtid;
#pragma unroll
                    for (int i = 0; i < 8; i++)
                        p[i * 128] = make_float4(acc[q * 32 + 4 * i], acc[q * 32 + 4 * i + 1], acc[q * 32 + 4 * i + 2], acc[q * 32 + 4 * i + 3]);
                }
            }
            __threadfence();
            asm volatile("bar.sync 3, 256;" ::: "memory");
            TL(7);
            if (w == 0 && wtid == 0) {
                atomicAdd(&g_rflag[tile], 1u);
                unsigned int spins = 0;
                while (ld_acquire(&g_rflag[tile]) < 4u) {
                    if (++spins > (1u << 26)) break;
                }
                if (atomicAdd(&g_rcons[tile], 1u) == 3u) {
                    g_rcons[tile] = 0u;
                    g_rflag[tile] = 0u;
                }
            }
            asm volatile("bar.sync 3, 256;" ::: "memory");
            TL(8);
            float r[32];
#pragma unroll
            for (int q = 0; q < 4; q++) {
                if (q == s2) {
#pragma unroll
                    for (int i = 0; i < 32; i++) r[i] = acc[q * 32 + i];
                }
            }
#pragma unroll
            for (int sp = 0; sp < 4; sp++) {
                if (sp != s2) {
                    const float4* p = reinterpret_cast<const float4*>(base + (size_t)sp * (128 * 256)) + ((s2 * 2 + w) * 8) * 128 + wtid;
#pragma unroll
                    for (int i = 0; i < 8; i++) {
                        const float4 t = __ldcg(p + i * 128);
                        r[4 * i] += t.x; r[4 * i + 1] += t.y; r[4 * i + 2] += t.z; r[4 * i + 3] += t.w;
                    }
                }
            }
            const int row = m * 128 + w * 64 + warp * 16 + (lane >> 2);
            __nv_bfloat16* op = out + (size_t)row * 2048 + blk * 1024 + n2 * 256 + s2 * 64 + (lane & 3) * 2;
#pragma unroll
            for (int g = 0; g < 8; g++) {
                *reinterpret_cast<uint32_t*>(op + g * 8) = pack_bf16(r[4 * g], r[4 * g + 1]);
                *reinterpret_cast<uint32_t*>(op + 8 * 2048 + g * 8) = pack_bf16(r[4 * g + 2], r[4 * g + 3]);
            }
        }
        TL(9);
        asm volatile("barrier.cluster.arrive.release.aligned;\n\tbarrier.cluster.wait.acquire.aligned;" ::: "memory");
    }
}

typedef CUresult (*EncodeFn)(CUtensorMap*, CUtensorMapDataType, cuuint32_t, void*, const cuuint64_t*, const cuuint64_t*,
                             const cuuint32_t*, const cuuint32_t*, CUtensorMapInterleave, CUtensorMapSwizzle,
                             CUtensorMapL2promotion, CUtensorMapFloatOOBfill);

static void make_map(EncodeFn fn, CUtensorMap* map, const void* ptr, uint64_t rows, uint64_t cols, uint32_t box_rows) {
    cuuint64_t dims[2] = {cols, rows};
    cuuint64_t strides[1] = {cols * 2};
    cuuint32_t box[2] = {64, box_rows};
    cuuint32_t estr[2] = {1, 1};
    fn(map, CU_TENSOR_MAP_DATA_TYPE_BFLOAT16, 2, const_cast<void*>(ptr), dims, strides, box, estr,
       CU_TENSOR_MAP_INTERLEAVE_NONE, CU_TENSOR_MAP_SWIZZLE_128B, CU_TENSOR_MAP_L2_PROMOTION_L2_128B, CU_TENSOR_MAP_FLOAT_OOB_FILL_NONE);
}

extern "C" void kernel_launch(void* const* d_in, const int* in_sizes, int n_in, void* d_out, int out_size) {
    static Maps maps;
    static bool ready = false;
    static void* cached[11];
    bool same = ready;
    for (int i = 0; i < 10 && same; i++) same = (cached[i] == d_in[i]);
    if (!same) {
        void* fnp = nullptr;
        cudaDriverEntryPointQueryResult qres;
        cudaGetDriverEntryPoint("cuTensorMapEncodeTiled", &fnp, cudaEnableDefault, &qres);
        EncodeFn fn = (EncodeFn)fnp;
        void* optr = nullptr;
        cudaGetSymbolAddress(&optr, g_o);
        for (int b = 0; b < 2; b++) {
            make_map(fn, &maps.x[b], d_in[5 * b + 0], 512, 1024, 128);
            make_map(fn, &maps.k[b], d_in[5 * b + 1], 16384, 128, 32);
            make_map(fn, &maps.v[b], d_in[5 * b + 2], 16384, 128, 32);
            make_map(fn, &maps.wq[b], d_in[5 * b + 3], 1024, 4096, 64);
            make_map(fn, &maps.wo[b], d_in[5 * b + 4], 4096, 1024, 64);
        }
        make_map(fn, &maps.o, optr, 1024, 4096, 64);
        cudaFuncSetAttribute(mha2_fused_kernel, cudaFuncAttributeMaxDynamicSharedMemorySize, SMEM_BYTES);
        for (int i = 0; i < 10; i++) cached[i] = d_in[i];
        ready = true;
    }
    mha2_fused_kernel<<<128, 384, SMEM_BYTES>>>(maps,
        (const __nv_bfloat16*)d_in[1], (const __nv_bfloat16*)d_in[2],
        (const __nv_bfloat16*)d_in[6], (const __nv_bfloat16*)d_in[7],
        (__nv_bfloat16*)d_out);
}
```

```cpp
#include <cuda_runtime.h>
#include <cuda_bf16.h>
#include <cuda.h>
#include <stdint.h>

#define DEVINL __device__ __forceinline__

constexpr int STAGES = 4;
constexpr int A_BYTES = 16384;
constexpr int B_BYTES = 32768;
constexpr int STAGE_BYTES = A_BYTES + B_BYTES;
constexpr int SMEM_BYTES = STAGES * STAGE_BYTES + 1024 + 256;

struct Maps {
    CUtensorMap x[2];
    CUtensorMap wq[2];
    CUtensorMap k[2];
    CUtensorMap v[2];
    CUtensorMap wo[2];
    CUtensorMap o;
};

__device__ __nv_bfloat16 g_o[2 * 512 * 4096];
__device__ float g_part[128 * 128 * 256];
__device__ unsigned int g_oflag[128];
__device__ unsigned int g_ocons[128];
__device__ unsigned int g_rflag[32];
__device__ unsigned int g_rcons[32];

#define TL(i)
DEVINL uint32_t smem_u32(const void* p) { return (uint32_t)__cvta_generic_to_shared(p); }

DEVINL void mbar_init(uint32_t bar, uint32_t count) {
    asm volatile("mbarrier.init.shared::cta.b64 [%0], %1;" ::"r"(bar), "r"(count));
}
DEVINL void mbar_expect_tx(uint32_t bar, uint32_t bytes) {
    asm volatile("mbarrier.arrive.expect_tx.shared::cta.b64 _, [%0], %1;" ::"r"(bar), "r"(bytes) : "memory");
}
DEVINL void mbar_arrive(uint32_t bar) {
    asm volatile("mbarrier.arrive.shared::cta.b64 _, [%0];" ::"r"(bar) : "memory");
}
DEVINL void mbar_arrive_remote(uint32_t bar, uint32_t cta) {
    asm volatile(
        "{\n\t.reg .b32 ra;\n\t"
        "mapa.shared::cluster.u32 ra, %0, %1;\n\t"
        "mbarrier.arrive.shared::cluster.b64 _, [ra];\n\t}"
        ::"r"(bar), "r"(cta) : "memory");
}
DEVINL void mbar_wait(uint32_t bar, uint32_t parity) {
    asm volatile(
        "{\n\t.reg .pred p;\n\t"
        "WAIT_LOOP:\n\t"
        "mbarrier.try_wait.parity.shared::cta.b64 p, [%0], %1, 0x989680;\n\t"
        "@p bra DONE;\n\t"
        "bra WAIT_LOOP;\n\t"
        "DONE:\n\t}"
        ::"r"(bar), "r"(parity) : "memory");
}
DEVINL void mbar_wait_cluster(uint32_t bar, uint32_t parity) {
    asm volatile(
        "{\n\t.reg .pred p;\n\t"
        "WAIT_LOOP:\n\t"
        "mbarrier.try_wait.parity.shared::cta.b64 p, [%0], %1, 0x989680;\n\t"
        "@p bra DONE;\n\t"
        "bra WAIT_LOOP;\n\t"
        "DONE:\n\t}"
        ::"r"(bar), "r"(parity) : "memory");
}

DEVINL void tma_load_2d(uint32_t dst, const CUtensorMap* map, int c0, int c1, uint32_t bar) {
    asm volatile(
        "cp.async.bulk.tensor.2d.shared::cluster.global.mbarrier::complete_tx::bytes [%0], [%1, {%3, %4}], [%2];"
        ::"r"(dst), "l"(map), "r"(bar), "r"(c0), "r"(c1) : "memory");
}
DEVINL void tma_load_2d_mc(uint32_t dst, const CUtensorMap* map, int c0, int c1, uint32_t bar, uint16_t mask) {
    asm volatile(
        "cp.async.bulk.tensor.2d.shared::cluster.global.mbarrier::complete_tx::bytes.multicast::cluster [%0], [%1, {%3, %4}], [%2], %5;"
        ::"r"(dst), "l"(map), "r"(bar), "r"(c0), "r"(c1), "h"(mask) : "memory");
}
DEVINL void tma_store_2d(const CUtensorMap* map, uint32_t src, int c0, int c1) {
    asm volatile(
        "cp.async.bulk.tensor.2d.global.shared::cta.bulk_group [%0, {%2, %3}], [%1];"
        ::"l"(map), "r"(src), "r"(c0), "r"(c1) : "memory");
}
DEVINL void l2_prefetch(const void* p, uint32_t bytes) {
    asm volatile("cp.async.bulk.prefetch.L2.global [%0], %1;" ::"l"(p), "r"(bytes) : "memory");
}
DEVINL void fence_proxy_async() { asm volatile("fence.proxy.async;" ::: "memory"); }
DEVINL void fence_proxy_async_smem() { asm volatile("fence.proxy.async.shared::cta;" ::: "memory"); }

DEVINL void wgmma_fence() { asm volatile("wgmma.fence.sync.aligned;" ::: "memory"); }
DEVINL void wgmma_commit() { asm volatile("wgmma.commit_group.sync.aligned;" ::: "memory"); }
template <int N> DEVINL void wgmma_wait() { asm volatile("wgmma.wait_group.sync.aligned %0;" ::"n"(N) : "memory"); }

DEVINL uint64_t make_desc(uint32_t addr, uint32_t lbo_bytes, uint32_t sbo_bytes) {
    uint64_t d = 0;
    d |= (uint64_t)((addr & 0x3FFFF) >> 4);
    d |= (uint64_t)((lbo_bytes >> 4) & 0x3FFF) << 16;
    d |= (uint64_t)((sbo_bytes >> 4) & 0x3FFF) << 32;
    d |= (uint64_t)1 << 62;
    return d;
}

#define R8(a, i) "+f"(a[i]), "+f"(a[i + 1]), "+f"(a[i + 2]), "+f"(a[i + 3]), "+f"(a[i + 4]), "+f"(a[i + 5]), "+f"(a[i + 6]), "+f"(a[i + 7])
#define R32(a, i) R8(a, i), R8(a, i + 8), R8(a, i + 16), R8(a, i + 24)

DEVINL void wgmma_m64n256k16_ss(float (&d)[128], uint64_t da, uint64_t db) {
    asm volatile(
        "wgmma.mma_async.sync.aligned.m64n256k16.f32.bf16.bf16 "
        "{%0,%1,%2,%3,%4,%5,%6,%7,%8,%9,%10,%11,%12,%13,%14,%15,%16,%17,%18,%19,%20,%21,%22,%23,%24,%25,%26,%27,%28,%29,%30,%31,"
        "%32,%33,%34,%35,%36,%37,%38,%39,%40,%41,%42,%43,%44,%45,%46,%47,%48,%49,%50,%51,%52,%53,%54,%55,%56,%57,%58,%59,%60,%61,%62,%63,"
        "%64,%65,%66,%67,%68,%69,%70,%71,%72,%73,%74,%75,%76,%77,%78,%79,%80,%81,%82,%83,%84,%85,%86,%87,%88,%89,%90,%91,%92,%93,%94,%95,"
        "%96,%97,%98,%99,%100,%101,%102,%103,%104,%105,%106,%107,%108,%109,%110,%111,%112,%113,%114,%115,%116,%117,%118,%119,%120,%121,%122,%123,%124,%125,%126,%127},"
        " %128, %129, 1, 1, 1, 0, 1;"
        : R32(d, 0), R32(d, 32), R32(d, 64), R32(d, 96)
        : "l"(da), "l"(db));
}
DEVINL void wgmma_m64n64k16_rs(float (&d)[32], uint32_t a0, uint32_t a1, uint32_t a2, uint32_t a3, uint64_t db, int scale_d) {
    asm volatile(
        "{\n\t.reg .pred p;\n\tsetp.ne.b32 p, %37, 0;\n\t"
        "wgmma.mma_async.sync.aligned.m64n64k16.f32.bf16.bf16 "
        "{%0,%1,%2,%3,%4,%5,%6,%7,%8,%9,%10,%11,%12,%13,%14,%15,%16,%17,%18,%19,%20,%21,%22,%23,%24,%25,%26,%27,%28,%29,%30,%31},"
        " {%32,%33,%34,%35}, %36, p, 1, 1, 0;\n\t}"
        : R32(d, 0)
        : "r"(a0), "r"(a1), "r"(a2), "r"(a3), "l"(db), "r"(scale_d));
}
DEVINL void wgmma_m64n128k16_rs(float (&d)[64], uint32_t a0, uint32_t a1, uint32_t a2, uint32_t a3, uint64_t db, int scale_d) {
    asm volatile(
        "{\n\t.reg .pred p;\n\tsetp.ne.b32 p, %69, 0;\n\t"
        "wgmma.mma_async.sync.aligned.m64n128k16.f32.bf16.bf16 "
        "{%0,%1,%2,%3,%4,%5,%6,%7,%8,%9,%10,%11,%12,%13,%14,%15,%16,%17,%18,%19,%20,%21,%22,%23,%24,%25,%26,%27,%28,%29,%30,%31,"
        "%32,%33,%34,%35,%36,%37,%38,%39,%40,%41,%42,%43,%44,%45,%46,%47,%48,%49,%50,%51,%52,%53,%54,%55,%56,%57,%58,%59,%60,%61,%62,%63},"
        " {%64,%65,%66,%67}, %68, p, 1, 1, 1;\n\t}"
        : R32(d, 0), R32(d, 32)
        : "r"(a0), "r"(a1), "r"(a2), "r"(a3), "l"(db), "r"(scale_d));
}

DEVINL uint32_t pack_bf16(float lo, float hi) {
    __nv_bfloat162 t = __floats2bfloat162_rn(lo, hi);
    return *reinterpret_cast<uint32_t*>(&t);
}
DEVINL void stmatrix_x4(uint32_t addr, uint32_t r0, uint32_t r1, uint32_t r2, uint32_t r3) {
    asm volatile("stmatrix.sync.aligned.m8n8.x4.shared.b16 [%0], {%1,%2,%3,%4};" ::"r"(addr), "r"(r0), "r"(r1), "r"(r2), "r"(r3) : "memory");
}
DEVINL unsigned int ld_acquire(const unsigned int* p) {
    unsigned int v;
    asm volatile("ld.acquire.gpu.global.u32 %0, [%1];" : "=r"(v) : "l"(p) : "memory");
    return v;
}

__global__ void __cluster_dims__(2, 1, 1) __launch_bounds__(384, 1)
mha2_fused_kernel(const __grid_constant__ Maps maps,
                  const __nv_bfloat16* __restrict__ kA, const __nv_bfloat16* __restrict__ vA,
                  const __nv_bfloat16* __restrict__ kB, const __nv_bfloat16* __restrict__ vB,
                  __nv_bfloat16* __restrict__ out)
{
    extern __shared__ uint8_t smem_raw[];
    const uint32_t smem_base = (smem_u32(smem_raw) + 1023u) & ~1023u;
    const uint32_t bar_base = smem_base + STAGES * STAGE_BYTES;
    auto full_bar = [&](int s) { return bar_base + 8u * s; };
    auto empty_bar = [&](int s) { return bar_base + 64u + 8u * s; };

    const int tid = threadIdx.x;
    const int wg = tid >> 7;
    uint32_t rank;
    asm volatile("mov.u32 %0, %%cluster_ctarank;" : "=r"(rank));
    const int cl = blockIdx.x >> 1;
    const int blk = cl >> 5;
    const int mp = (cl >> 4) & 1;
    const int m = mp * 2 + (int)rank;
    const int hp = cl & 15;
    const int n2 = hp & 3;
    const int s2 = hp >> 2;

    if (tid == 0) {
        for (int s = 0; s < STAGES; s++) {
            mbar_init(full_bar(s), 1);
            mbar_init(empty_bar(s), 4);
        }
        mbar_init(bar_base + 128u, 2);
        asm volatile("fence.mbarrier_init.release.cluster;" ::: "memory");
    }
    __syncthreads();
    asm volatile("barrier.cluster.arrive.release.aligned;\n\tbarrier.cluster.wait.acquire.aligned;" ::: "memory");

    TL(0);
    if (wg == 2) {
        asm volatile("setmaxnreg.dec.sync.aligned.u32 40;");
        if (tid >= 288 && tid < 352) {
            const int hw = (tid - 288) >> 5;
            for (int hh = 0; hh < 2; hh++) {
                asm volatile("bar.sync %0, 160;" ::"r"(4 + hw) : "memory");
                if ((tid & 31) == 0) {
                    const uint32_t so = smem_base + (2 * hh) * STAGE_BYTES + hw * 8192;
                    const int col = (hp * 2 + hh) * 128;
                    const int row = blk * 512 + m * 128 + hw * 64;
                    tma_store_2d(&maps.o, so, col, row);
                    tma_store_2d(&maps.o, so + STAGE_BYTES, col + 64, row);
                    asm volatile("cp.async.bulk.commit_group;" ::: "memory");
                }
            }
            if ((tid & 31) == 0) {
                asm volatile("cp.async.bulk.wait_group 0;" ::: "memory");
                mbar_arrive(bar_base + 128u);
                __threadfence();
                atomicAdd(&g_oflag[(blk * 4 + m) * 16 + hp], 1u);
            }
        }
        if (tid == 256) {
            int it = 0;
            auto acquire = [&](uint32_t bytes) {
                const int st = it % STAGES;
                mbar_wait_cluster(empty_bar(st), ((it / STAGES) & 1) ^ 1);
                mbar_expect_tx(full_bar(st), bytes);
                return st;
            };
            const __nv_bfloat16* kp = blk ? kB : kA;
            const __nv_bfloat16* vp = blk ? vB : vA;
            for (int kb = 0; kb < 16; kb++, it++) {
                const int st = acquire(STAGE_BYTES);
                const uint32_t sa = smem_base + st * STAGE_BYTES;
                tma_load_2d(sa, &maps.x[blk], kb * 64, m * 128, full_bar(st));
                const uint32_t sb = sa + A_BYTES + rank * 16384;
                tma_load_2d_mc(sb, &maps.wq[blk], hp * 256 + rank * 128, kb * 64, full_bar(st), 3);
                tma_load_2d_mc(sb + 8192, &maps.wq[blk], hp * 256 + rank * 128 + 64, kb * 64, full_bar(st), 3);
                if (kb >= 2 && kb < 10) {
                    const int j = kb - 2;
                    const int b = m * 4 + (j >> 1);
                    const __nv_bfloat16* p = ((j & 1) ? vp : kp) + ((size_t)(b * 32 + hp * 2)) * 4096;
                    l2_prefetch(p, 16384);
                }
            }
            TL(1);
            for (int j = 0; j < 4; j++, it++) {
                const int st = acquire(32768);
                const uint32_t sk = smem_base + st * STAGE_BYTES + A_BYTES;
                const int h = hp * 2 + (j >> 1);
                for (int bi = 0; bi < 2; bi++) {
                    const int b = m * 4 + (j & 1) * 2 + bi;
                    const int row = (b * 32 + h) * 32;
                    for (int dh = 0; dh < 2; dh++) {
                        tma_load_2d(sk + dh * 8192 + bi * 4096, &maps.k[blk], dh * 64, row, full_bar(st));
                        tma_load_2d(sk + 16384 + dh * 8192 + bi * 4096, &maps.v[blk], dh * 64, row, full_bar(st));
                    }
                }
            }
            TL(2);
            const int it0 = it;
            for (int kb = 0; kb < 4; kb++, it++) {
                const int st = acquire(B_BYTES);
                const uint32_t sb = smem_base + st * STAGE_BYTES + A_BYTES + rank * 16384;
                const int kk = hp * 256 + kb * 64;
                tma_load_2d_mc(sb, &maps.wo[blk], n2 * 256 + rank * 128, kk, full_bar(st), 3);
                tma_load_2d_mc(sb + 8192, &maps.wo[blk], n2 * 256 + rank * 128 + 64, kk, full_bar(st), 3);
            }
            TL(3);
            for (int kb = 4; kb < 16; kb++, it++) {
                if (kb == 5) TL(5);
                if (kb == 9) TL(6);
                if (kb == 13) TL(7);
                const int st = acquire(STAGE_BYTES);
                const uint32_t sa = smem_base + st * STAGE_BYTES;
                const uint32_t sb = sa + A_BYTES + rank * 16384;
                const int hpk = s2 * 4 + ((n2 + (kb >> 2)) & 3);
                const int kk = hpk * 256 + (kb & 3) * 64;
                tma_load_2d_mc(sb, &maps.wo[blk], n2 * 256 + rank * 128, kk, full_bar(st), 3);
                tma_load_2d_mc(sb + 8192, &maps.wo[blk], n2 * 256 + rank * 128 + 64, kk, full_bar(st), 3);
                if (kb == 4) mbar_wait(bar_base + 128u, 0);
                if ((kb & 3) == 0) {
                    const int fi = (blk * 4 + m) * 16 + hpk;
                    unsigned int spins = 0;
                    while (ld_acquire(&g_oflag[fi]) < 2u) {
                        if (++spins > (1u << 26)) break;
                    }
                    if (atomicAdd(&g_ocons[fi], 1u) == 2u) {
                        g_ocons[fi] = 0u;
                        g_oflag[fi] = 0u;
                    }
                    fence_proxy_async();
                }
                tma_load_2d(sa, &maps.o, kk, blk * 512 + m * 128, full_bar(st));
                tma_load_2d(sa + 8192, &maps.o, kk, blk * 512 + m * 128 + 64, full_bar(st));
            }
        }
        __syncwarp();
        TL(9);
        asm volatile("barrier.cluster.arrive.release.aligned;\n\tbarrier.cluster.wait.acquire.aligned;" ::: "memory");
    } else {
        asm volatile("setmaxnreg.inc.sync.aligned.u32 232;");
        const int w = wg;
        const int wtid = tid & 127;
        const int warp = wtid >> 5, lane = tid & 31;
        int it = 0;
        auto release = [&](int st) {
            if (wtid == 0) {
                mbar_arrive(empty_bar(st));
                mbar_arrive_remote(empty_bar(st), rank ^ 1);
            }
        };
        auto mainloop = [&](float (&acc)[128]) {
#pragma unroll
            for (int i = 0; i < 128; i++) acc[i] = 0.f;
            for (int kb = 0; kb < 16; kb++, it++) {
                const int st = it % STAGES;
                mbar_wait(full_bar(st), (it / STAGES) & 1);
                const uint32_t sa = smem_base + st * STAGE_BYTES + w * 8192;
                const uint32_t sb = smem_base + st * STAGE_BYTES + A_BYTES;
                wgmma_fence();
#pragma unroll
                for (int k = 0; k < 4; k++) {
                    wgmma_m64n256k16_ss(acc, make_desc(sa + k * 32, 16, 1024), make_desc(sb + k * 2048, 8192, 1024));
                }
                wgmma_commit();
                if (kb > 0) {
                    wgmma_wait<1>();
                    release((it - 1) % STAGES);
                }
            }
            wgmma_wait<0>();
            release((it - 1) % STAGES);
        };

        float acc[128];
        mainloop(acc);
        TL(1);

        uint32_t qf[64];
#pragma unroll
        for (int i = 0; i < 64; i++) qf[i] = pack_bf16(acc[2 * i], acc[2 * i + 1]);
#pragma unroll
        for (int j = 0; j < 4; j++, it++) {
            const int st = it % STAGES;
            mbar_wait(full_bar(st), (it / STAGES) & 1);
            if ((j & 1) == w) {
                const int hh = j >> 1;
                if (hh == 1) TL(10);
                const uint32_t sk = smem_base + st * STAGE_BYTES + A_BYTES;
                const uint32_t sv = sk + 16384;
                const uint32_t so = smem_base + (2 * hh) * STAGE_BYTES + w * 8192;
                float sc[32];
                wgmma_fence();
#pragma unroll
                for (int t = 0; t < 8; t++) {
                    const int g = hh * 16 + 2 * t;
                    wgmma_m64n64k16_rs(sc, qf[2 * g], qf[2 * g + 1], qf[2 * g + 2], qf[2 * g + 3],
                                       make_desc(sk + (t >> 2) * 8192 + (t & 3) * 32, 16, 1024), t > 0);
                }
                wgmma_commit();
                wgmma_wait<0>();
                const bool hi = warp >= 2;
                float v0[8], v1[8];
#pragma unroll
                for (int g = 0; g < 4; g++) {
                    v0[2 * g] = hi ? sc[(g + 4) * 4 + 0] : sc[g * 4 + 0];
                    v0[2 * g + 1] = hi ? sc[(g + 4) * 4 + 1] : sc[g * 4 + 1];
                    v1[2 * g] = hi ? sc[(g + 4) * 4 + 2] : sc[g * 4 + 2];
                    v1[2 * g + 1] = hi ? sc[(g + 4) * 4 + 3] : sc[g * 4 + 3];
                }
                float m0 = v0[0], m1 = v1[0];
#pragma unroll
                for (int i = 1; i < 8; i++) { m0 = fmaxf(m0, v0[i]); m1 = fmaxf(m1, v1[i]); }
                m0 = fmaxf(m0, __shfl_xor_sync(0xffffffffu, m0, 1));
                m0 = fmaxf(m0, __shfl_xor_sync(0xffffffffu, m0, 2));
                m1 = fmaxf(m1, __shfl_xor_sync(0xffffffffu, m1, 1));
                m1 = fmaxf(m1, __shfl_xor_sync(0xffffffffu, m1, 2));
                const float cs = 0.08838834764831845f * 1.4426950408889634f;
                float s0 = 0.f, s1 = 0.f;
#pragma unroll
                for (int i = 0; i < 8; i++) {
                    v0[i] = exp2f((v0[i] - m0) * cs); s0 += v0[i];
                    v1[i] = exp2f((v1[i] - m1) * cs); s1 += v1[i];
                }
                s0 += __shfl_xor_sync(0xffffffffu, s0, 1);
                s0 += __shfl_xor_sync(0xffffffffu, s0, 2);
                s1 += __shfl_xor_sync(0xffffffffu, s1, 1);
                s1 += __shfl_xor_sync(0xffffffffu, s1, 2);
                const float i0 = 1.f / s0, i1 = 1.f / s1;
                uint32_t pf[8];
#pragma unroll
                for (int t = 0; t < 2; t++) {
                    pf[4 * t + 0] = pack_bf16(v0[4 * t + 0] * i0, v0[4 * t + 1] * i0);
                    pf[4 * t + 1] = pack_bf16(v1[4 * t + 0] * i1, v1[4 * t + 1] * i1);
                    pf[4 * t + 2] = pack_bf16(v0[4 * t + 2] * i0, v0[4 * t + 3] * i0);
                    pf[4 * t + 3] = pack_bf16(v1[4 * t + 2] * i1, v1[4 * t + 3] * i1);
                }
                float oc[64];
                wgmma_fence();
#pragma unroll
                for (int t = 0; t < 4; t++) {
                    const bool val = (t >> 1) == (hi ? 1 : 0);
                    const int tt = t & 1;
                    wgmma_m64n128k16_rs(oc, val ? pf[4 * tt + 0] : 0u, val ? pf[4 * tt + 1] : 0u, val ? pf[4 * tt + 2] : 0u, val ? pf[4 * tt + 3] : 0u,
                                        make_desc(sv + t * 2048, 8192, 1024), t > 0);
                }
                wgmma_commit();
                wgmma_wait<0>();
#pragma unroll
                for (int c = 0; c < 8; c++) {
                    const uint32_t r0 = pack_bf16(oc[8 * c + 0], oc[8 * c + 1]);
                    const uint32_t r1 = pack_bf16(oc[8 * c + 2], oc[8 * c + 3]);
                    const uint32_t r2 = pack_bf16(oc[8 * c + 4], oc[8 * c + 5]);
                    const uint32_t r3 = pack_bf16(oc[8 * c + 6], oc[8 * c + 7]);
                    const int row = warp * 16 + (lane & 7) + ((lane >> 3) & 1) * 8;
                    const int chunk = (c & 3) * 2 + (lane >> 4);
                    const uint32_t addr = so + (c >> 2) * STAGE_BYTES + row * 128 + ((chunk ^ (row & 7)) << 4);
                    stmatrix_x4(addr, r0, r1, r2, r3);
                }
                fence_proxy_async_smem();
                asm volatile("bar.arrive %0, 160;" ::"r"(4 + w) : "memory");
                if (hh == 1) TL(11);
            }
            release(st);
            TL(2 + j);
        }

        asm volatile("bar.sync %0, 128;" ::"r"(1 + w) : "memory");
        mainloop(acc);
        TL(6);

        {
            const int tile = (blk * 4 + m) * 4 + n2;
            float* base = g_part + (size_t)(tile * 4) * (128 * 256);
#pragma unroll
            for (int q = 0; q < 4; q++) {
                if (q != s2) {
                    float4* p = reinterpret_cast<float4*>(base + (size_t)s2 * (128 * 256)) + ((q * 2 + w) * 8) * 128 + wtid;
#pragma unroll
                    for (int i = 0; i < 8; i++)
                        p[i * 128] = make_float4(acc[q * 32 + 4 * i], acc[q * 32 + 4 * i + 1], acc[q * 32 + 4 * i + 2], acc[q * 32 + 4 * i + 3]);
                }
            }
            asm volatile("bar.sync 3, 256;" ::: "memory");
            TL(7);
            if (w == 0 && wtid == 0) {
                __threadfence();
                atomicAdd(&g_rflag[tile], 1u);
                unsigned int spins = 0;
                while (ld_acquire(&g_rflag[tile]) < 4u) {
                    if (++spins > (1u << 26)) break;
                }
                if (atomicAdd(&g_rcons[tile], 1u) == 3u) {
                    g_rcons[tile] = 0u;
                    g_rflag[tile] = 0u;
                }
            }
            asm volatile("bar.sync 3, 256;" ::: "memory");
            TL(8);
            float r[32];
#pragma unroll
            for (int q = 0; q < 4; q++) {
                if (q == s2) {
#pragma unroll
                    for (int i = 0; i < 32; i++) r[i] = acc[q * 32 + i];
                }
            }
#pragma unroll
            for (int sp = 0; sp < 4; sp++) {
                if (sp != s2) {
                    const float4* p = reinterpret_cast<const float4*>(base + (size_t)sp * (128 * 256)) + ((s2 * 2 + w) * 8) * 128 + wtid;
#pragma unroll
                    for (int i = 0; i < 8; i++) {
                        const float4 t = __ldcg(p + i * 128);
                        r[4 * i] += t.x; r[4 * i + 1] += t.y; r[4 * i + 2] += t.z; r[4 * i + 3] += t.w;
                    }
                }
            }
            const int row = m * 128 + w * 64 + warp * 16 + (lane >> 2);
            __nv_bfloat16* op = out + (size_t)row * 2048 + blk * 1024 + n2 * 256 + s2 * 64 + (lane & 3) * 2;
#pragma unroll
            for (int g = 0; g < 8; g++) {
                *reinterpret_cast<uint32_t*>(op + g * 8) = pack_bf16(r[4 * g], r[4 * g + 1]);
                *reinterpret_cast<uint32_t*>(op + 8 * 2048 + g * 8) = pack_bf16(r[4 * g + 2], r[4 * g + 3]);
            }
        }
        TL(9);
        asm volatile("barrier.cluster.arrive.release.aligned;\n\tbarrier.cluster.wait.acquire.aligned;" ::: "memory");
    }
}

typedef CUresult (*EncodeFn)(CUtensorMap*, CUtensorMapDataType, cuuint32_t, void*, const cuuint64_t*, const cuuint64_t*,
                             const cuuint32_t*, const cuuint32_t*, CUtensorMapInterleave, CUtensorMapSwizzle,
                             CUtensorMapL2promotion, CUtensorMapFloatOOBfill);

static void make_map(EncodeFn fn, CUtensorMap* map, const void* ptr, uint64_t rows, uint64_t cols, uint32_t box_rows) {
    cuuint64_t dims[2] = {cols, rows};
    cuuint64_t strides[1] = {cols * 2};
    cuuint32_t box[2] = {64, box_rows};
    cuuint32_t estr[2] = {1, 1};
    fn(map, CU_TENSOR_MAP_DATA_TYPE_BFLOAT16, 2, const_cast<void*>(ptr), dims, strides, box, estr,
       CU_TENSOR_MAP_INTERLEAVE_NONE, CU_TENSOR_MAP_SWIZZLE_128B, CU_TENSOR_MAP_L2_PROMOTION_L2_128B, CU_TENSOR_MAP_FLOAT_OOB_FILL_NONE);
}

extern "C" void kernel_launch(void* const* d_in, const int* in_sizes, int n_in, void* d_out, int out_size) {
    static Maps maps;
    static bool ready = false;
    static void* cached[11];
    bool same = ready;
    for (int i = 0; i < 10 && same; i++) same = (cached[i] == d_in[i]);
    if (!same) {
        void* fnp = nullptr;
        cudaDriverEntryPointQueryResult qres;
        cudaGetDriverEntryPoint("cuTensorMapEncodeTiled", &fnp, cudaEnableDefault, &qres);
        EncodeFn fn = (EncodeFn)fnp;
        void* optr = nullptr;
        cudaGetSymbolAddress(&optr, g_o);
        for (int b = 0; b < 2; b++) {
            make_map(fn, &maps.x[b], d_in[5 * b + 0], 512, 1024, 128);
            make_map(fn, &maps.k[b], d_in[5 * b + 1], 16384, 128, 32);
            make_map(fn, &maps.v[b], d_in[5 * b + 2], 16384, 128, 32);
            make_map(fn, &maps.wq[b], d_in[5 * b + 3], 1024, 4096, 64);
            make_map(fn, &maps.wo[b], d_in[5 * b + 4], 4096, 1024, 64);
        }
        make_map(fn, &maps.o, optr, 1024, 4096, 64);
        cudaFuncSetAttribute(mha2_fused_kernel, cudaFuncAttributeMaxDynamicSharedMemorySize, SMEM_BYTES);
        for (int i = 0; i < 10; i++) cached[i] = d_in[i];
        ready = true;
    }
    mha2_fused_kernel<<<128, 384, SMEM_BYTES>>>(maps,
        (const __nv_bfloat16*)d_in[1], (const __nv_bfloat16*)d_in[2],
        (const __nv_bfloat16*)d_in[6], (const __nv_bfloat16*)d_in[7],
        (__nv_bfloat16*)d_out);
}
```

```cpp
#include <cuda_runtime.h>
#include <cuda_bf16.h>
#include <cuda.h>
#include <stdint.h>

#define DEVINL __device__ __forceinline__
#define PF_ON 1

constexpr int STAGES = 3;
constexpr int A_BYTES = 16384;
constexpr int B_BYTES = 32768;
constexpr int STAGE_BYTES = A_BYTES + B_BYTES;
constexpr int KBUF_BYTES = 65536;
constexpr int SMEM_BYTES = STAGES * STAGE_BYTES + KBUF_BYTES + 1024 + 256;

struct Maps {
    CUtensorMap x[2];
    CUtensorMap wq[2];
    CUtensorMap k[2];
    CUtensorMap v[2];
    CUtensorMap wo[2];
    CUtensorMap o;
};

__device__ __nv_bfloat16 g_o[2 * 512 * 4096];
__device__ float g_part[128 * 128 * 256];
__device__ unsigned int g_oflag[128];
__device__ unsigned int g_ocons[128];
__device__ unsigned int g_rflag[32];
__device__ unsigned int g_rcons[32];

#define TL(i)
DEVINL uint32_t smem_u32(const void* p) { return (uint32_t)__cvta_generic_to_shared(p); }

DEVINL void mbar_init(uint32_t bar, uint32_t count) {
    asm volatile("mbarrier.init.shared::cta.b64 [%0], %1;" ::"r"(bar), "r"(count));
}
DEVINL void mbar_expect_tx(uint32_t bar, uint32_t bytes) {
    asm volatile("mbarrier.arrive.expect_tx.shared::cta.b64 _, [%0], %1;" ::"r"(bar), "r"(bytes) : "memory");
}
DEVINL void mbar_arrive(uint32_t bar) {
    asm volatile("mbarrier.arrive.shared::cta.b64 _, [%0];" ::"r"(bar) : "memory");
}
DEVINL void mbar_arrive_remote(uint32_t bar, uint32_t cta) {
    asm volatile(
        "{\n\t.reg .b32 ra;\n\t"
        "mapa.shared::cluster.u32 ra, %0, %1;\n\t"
        "mbarrier.arrive.shared::cluster.b64 _, [ra];\n\t}"
        ::"r"(bar), "r"(cta) : "memory");
}
DEVINL void mbar_wait(uint32_t bar, uint32_t parity) {
    asm volatile(
        "{\n\t.reg .pred p;\n\t"
        "WAIT_LOOP:\n\t"
        "mbarrier.try_wait.parity.shared::cta.b64 p, [%0], %1, 0x989680;\n\t"
        "@p bra DONE;\n\t"
        "bra WAIT_LOOP;\n\t"
        "DONE:\n\t}"
        ::"r"(bar), "r"(parity) : "memory");
}
DEVINL void mbar_wait_cluster(uint32_t bar, uint32_t parity) {
    asm volatile(
        "{\n\t.reg .pred p;\n\t"
        "WAIT_LOOP:\n\t"
        "mbarrier.try_wait.parity.shared::cta.b64 p, [%0], %1, 0x989680;\n\t"
        "@p bra DONE;\n\t"
        "bra WAIT_LOOP;\n\t"
        "DONE:\n\t}"
        ::"r"(bar), "r"(parity) : "memory");
}

DEVINL void tma_load_2d(uint32_t dst, const CUtensorMap* map, int c0, int c1, uint32_t bar) {
    asm volatile(
        "cp.async.bulk.tensor.2d.shared::cluster.global.mbarrier::complete_tx::bytes [%0], [%1, {%3, %4}], [%2];"
        ::"r"(dst), "l"(map), "r"(bar), "r"(c0), "r"(c1) : "memory");
}
DEVINL void tma_load_2d_mc(uint32_t dst, const CUtensorMap* map, int c0, int c1, uint32_t bar, uint16_t mask) {
    asm volatile(
        "cp.async.bulk.tensor.2d.shared::cluster.global.mbarrier::complete_tx::bytes.multicast::cluster [%0], [%1, {%3, %4}], [%2], %5;"
        ::"r"(dst), "l"(map), "r"(bar), "r"(c0), "r"(c1), "h"(mask) : "memory");
}
DEVINL void tma_store_2d(const CUtensorMap* map, uint32_t src, int c0, int c1) {
    asm volatile(
        "cp.async.bulk.tensor.2d.global.shared::cta.bulk_group [%0, {%2, %3}], [%1];"
        ::"l"(map), "r"(src), "r"(c0), "r"(c1) : "memory");
}
DEVINL void l2_prefetch(const void* p, uint32_t bytes) {
    asm volatile("cp.async.bulk.prefetch.L2.global [%0], %1;" ::"l"(p), "r"(bytes) : "memory");
}
DEVINL void fence_proxy_async() { asm volatile("fence.proxy.async;" ::: "memory"); }
DEVINL void fence_proxy_async_smem() { asm volatile("fence.proxy.async.shared::cta;" ::: "memory"); }

DEVINL void wgmma_fence() { asm volatile("wgmma.fence.sync.aligned;" ::: "memory"); }
DEVINL void wgmma_commit() { asm volatile("wgmma.commit_group.sync.aligned;" ::: "memory"); }
template <int N> DEVINL void wgmma_wait() { asm volatile("wgmma.wait_group.sync.aligned %0;" ::"n"(N) : "memory"); }

DEVINL uint64_t make_desc(uint32_t addr, uint32_t lbo_bytes, uint32_t sbo_bytes) {
    uint64_t d = 0;
    d |= (uint64_t)((addr & 0x3FFFF) >> 4);
    d |= (uint64_t)((lbo_bytes >> 4) & 0x3FFF) << 16;
    d |= (uint64_t)((sbo_bytes >> 4) & 0x3FFF) << 32;
    d |= (uint64_t)1 << 62;
    return d;
}

#define R8(a, i) "+f"(a[i]), "+f"(a[i + 1]), "+f"(a[i + 2]), "+f"(a[i + 3]), "+f"(a[i + 4]), "+f"(a[i + 5]), "+f"(a[i + 6]), "+f"(a[i + 7])
#define R32(a, i) R8(a, i), R8(a, i + 8), R8(a, i + 16), R8(a, i + 24)

DEVINL void wgmma_m64n256k16_ss(float (&d)[128], uint64_t da, uint64_t db) {
    asm volatile(
        "wgmma.mma_async.sync.aligned.m64n256k16.f32.bf16.bf16 "
        "{%0,%1,%2,%3,%4,%5,%6,%7,%8,%9,%10,%11,%12,%13,%14,%15,%16,%17,%18,%19,%20,%21,%22,%23,%24,%25,%26,%27,%28,%29,%30,%31,"
        "%32,%33,%34,%35,%36,%37,%38,%39,%40,%41,%42,%43,%44,%45,%46,%47,%48,%49,%50,%51,%52,%53,%54,%55,%56,%57,%58,%59,%60,%61,%62,%63,"
        "%64,%65,%66,%67,%68,%69,%70,%71,%72,%73,%74,%75,%76,%77,%78,%79,%80,%81,%82,%83,%84,%85,%86,%87,%88,%89,%90,%91,%92,%93,%94,%95,"
        "%96,%97,%98,%99,%100,%101,%102,%103,%104,%105,%106,%107,%108,%109,%110,%111,%112,%113,%114,%115,%116,%117,%118,%119,%120,%121,%122,%123,%124,%125,%126,%127},"
        " %128, %129, 1, 1, 1, 0, 1;"
        : R32(d, 0), R32(d, 32), R32(d, 64), R32(d, 96)
        : "l"(da), "l"(db));
}
DEVINL void wgmma_m64n64k16_rs(float (&d)[32], uint32_t a0, uint32_t a1, uint32_t a2, uint32_t a3, uint64_t db, int scale_d) {
    asm volatile(
        "{\n\t.reg .pred p;\n\tsetp.ne.b32 p, %37, 0;\n\t"
        "wgmma.mma_async.sync.aligned.m64n64k16.f32.bf16.bf16 "
        "{%0,%1,%2,%3,%4,%5,%6,%7,%8,%9,%10,%11,%12,%13,%14,%15,%16,%17,%18,%19,%20,%21,%22,%23,%24,%25,%26,%27,%28,%29,%30,%31},"
        " {%32,%33,%34,%35}, %36, p, 1, 1, 0;\n\t}"
        : R32(d, 0)
        : "r"(a0), "r"(a1), "r"(a2), "r"(a3), "l"(db), "r"(scale_d));
}
DEVINL void wgmma_m64n128k16_rs(float (&d)[64], uint32_t a0, uint32_t a1, uint32_t a2, uint32_t a3, uint64_t db, int scale_d) {
    asm volatile(
        "{\n\t.reg .pred p;\n\tsetp.ne.b32 p, %69, 0;\n\t"
        "wgmma.mma_async.sync.aligned.m64n128k16.f32.bf16.bf16 "
        "{%0,%1,%2,%3,%4,%5,%6,%7,%8,%9,%10,%11,%12,%13,%14,%15,%16,%17,%18,%19,%20,%21,%22,%23,%24,%25,%26,%27,%28,%29,%30,%31,"
        "%32,%33,%34,%35,%36,%37,%38,%39,%40,%41,%42,%43,%44,%45,%46,%47,%48,%49,%50,%51,%52,%53,%54,%55,%56,%57,%58,%59,%60,%61,%62,%63},"
        " {%64,%65,%66,%67}, %68, p, 1, 1, 1;\n\t}"
        : R32(d, 0), R32(d, 32)
        : "r"(a0), "r"(a1), "r"(a2), "r"(a3), "l"(db), "r"(scale_d));
}

DEVINL uint32_t pack_bf16(float lo, float hi) {
    __nv_bfloat162 t = __floats2bfloat162_rn(lo, hi);
    return *reinterpret_cast<uint32_t*>(&t);
}
DEVINL void stmatrix_x4(uint32_t addr, uint32_t r0, uint32_t r1, uint32_t r2, uint32_t r3) {
    asm volatile("stmatrix.sync.aligned.m8n8.x4.shared.b16 [%0], {%1,%2,%3,%4};" ::"r"(addr), "r"(r0), "r"(r1), "r"(r2), "r"(r3) : "memory");
}
DEVINL unsigned int ld_acquire(const unsigned int* p) {
    unsigned int v;
    asm volatile("ld.acquire.gpu.global.u32 %0, [%1];" : "=r"(v) : "l"(p) : "memory");
    return v;
}

__global__ void __cluster_dims__(2, 1, 1) __launch_bounds__(384, 1)
mha2_fused_kernel(const __grid_constant__ Maps maps,
                  const __nv_bfloat16* __restrict__ kA, const __nv_bfloat16* __restrict__ vA,
                  const __nv_bfloat16* __restrict__ kB, const __nv_bfloat16* __restrict__ vB,
                  __nv_bfloat16* __restrict__ out)
{
    extern __shared__ uint8_t smem_raw[];
    const uint32_t smem_base = (smem_u32(smem_raw) + 1023u) & ~1023u;
    const uint32_t kbuf = smem_base + STAGES * STAGE_BYTES;
    const uint32_t bar_base = kbuf + KBUF_BYTES;
    auto full_bar = [&](int s) { return bar_base + 8u * s; };
    auto empty_bar = [&](int s) { return bar_base + 64u + 8u * s; };

    const int tid = threadIdx.x;
    const int wg = tid >> 7;
    uint32_t rank;
    asm volatile("mov.u32 %0, %%cluster_ctarank;" : "=r"(rank));
    const int cl = blockIdx.x >> 1;
    const int blk = cl >> 5;
    const int mp = (cl >> 4) & 1;
    const int m = mp * 2 + (int)rank;
    const int hp = cl & 15;
    const int n2 = hp & 3;
    const int s2 = hp >> 2;

    if (tid == 0) {
        for (int s = 0; s < STAGES; s++) {
            mbar_init(full_bar(s), 1);
            mbar_init(empty_bar(s), 4);
        }
        mbar_init(bar_base + 136u, 1);
        mbar_init(bar_base + 144u, 1);
        asm volatile("fence.mbarrier_init.release.cluster;" ::: "memory");
    }
    __syncthreads();
    asm volatile("barrier.cluster.arrive.release.aligned;\n\tbarrier.cluster.wait.acquire.aligned;" ::: "memory");

    TL(0);
    if (wg == 2) {
        asm volatile("setmaxnreg.dec.sync.aligned.u32 40;");
        if (tid >= 288 && tid < 352) {
            const int hw = (tid - 288) >> 5;
            for (int hh = 0; hh < 2; hh++) {
                asm volatile("bar.sync %0, 160;" ::"r"(4 + hw) : "memory");
                if ((tid & 31) == 0) {
                    const uint32_t so = kbuf + (hw * 2 + hh) * 16384;
                    const int col = (hp * 2 + hh) * 128;
                    const int row = blk * 512 + m * 128 + hw * 64;
                    tma_store_2d(&maps.o, so, col, row);
                    tma_store_2d(&maps.o, so + 8192, col + 64, row);
                    asm volatile("cp.async.bulk.commit_group;" ::: "memory");
                }
            }
            if ((tid & 31) == 0) {
                asm volatile("cp.async.bulk.wait_group 0;" ::: "memory");
                __threadfence();
                atomicAdd(&g_oflag[(blk * 4 + m) * 16 + hp], 1u);
            }
        }
        if (tid == 256) {
            int it = 0;
            auto acquire = [&](uint32_t bytes) {
                const int st = it % STAGES;
                mbar_wait_cluster(empty_bar(st), ((it / STAGES) & 1) ^ 1);
                mbar_expect_tx(full_bar(st), bytes);
                return st;
            };
            const __nv_bfloat16* kp = blk ? kB : kA;
            const __nv_bfloat16* vp = blk ? vB : vA;
            for (int kb = 0; kb < 16; kb++, it++) {
                const int st = acquire(STAGE_BYTES);
                const uint32_t sa = smem_base + st * STAGE_BYTES;
                tma_load_2d(sa, &maps.x[blk], kb * 64, m * 128, full_bar(st));
                const uint32_t sb = sa + A_BYTES + rank * 16384;
                tma_load_2d_mc(sb, &maps.wq[blk], hp * 256 + rank * 128, kb * 64, full_bar(st), 3);
                tma_load_2d_mc(sb + 8192, &maps.wq[blk], hp * 256 + rank * 128 + 64, kb * 64, full_bar(st), 3);
                if (kb < 8) {
                    const int j = kb;
                    const int hh = j >> 2, bq = j & 3;
                    if (bq == 0) mbar_expect_tx(bar_base + 136u + 8u * hh, 32768);
                    const int row = ((m * 4 + bq) * 32 + hp * 2 + hh) * 32;
                    const uint32_t dk = kbuf + ((bq >> 1) * 2 + hh) * 16384 + (bq & 1) * 4096;
                    tma_load_2d(dk, &maps.k[blk], 0, row, bar_base + 136u + 8u * hh);
                    tma_load_2d(dk + 8192, &maps.k[blk], 64, row, bar_base + 136u + 8u * hh);
                } else if (PF_ON) {
                    const int j = kb - 8;
                    const __nv_bfloat16* p = vp + ((size_t)((m * 4 + (j & 3)) * 32 + hp * 2 + (j >> 2))) * 4096;
                    l2_prefetch(p, 8192);
                }
            }
            TL(1);
            for (int hh = 0; hh < 2; hh++, it++) {
                const int st = acquire(32768);
                TL(10 + hh);
                const uint32_t sv = smem_base + st * STAGE_BYTES + A_BYTES;
                for (int bq = 0; bq < 4; bq++) {
                    const int row = ((m * 4 + bq) * 32 + hp * 2 + hh) * 32;
                    const uint32_t dv = sv + (bq >> 1) * 16384 + (bq & 1) * 4096;
                    tma_load_2d(dv, &maps.v[blk], 0, row, full_bar(st));
                    tma_load_2d(dv + 8192, &maps.v[blk], 64, row, full_bar(st));
                }
            }
            TL(2);
            for (int kb = 0; kb < 4; kb++, it++) {
                const int st = acquire(B_BYTES);
                const uint32_t sb = smem_base + st * STAGE_BYTES + A_BYTES + rank * 16384;
                const int kk = hp * 256 + kb * 64;
                tma_load_2d_mc(sb, &maps.wo[blk], n2 * 256 + rank * 128, kk, full_bar(st), 3);
                tma_load_2d_mc(sb + 8192, &maps.wo[blk], n2 * 256 + rank * 128 + 64, kk, full_bar(st), 3);
            }
            TL(3);
            for (int kb = 4; kb < 16; kb++, it++) {
                if (kb == 5) TL(5);
                if (kb == 9) TL(6);
                if (kb == 13) TL(7);
                const int st = acquire(STAGE_BYTES);
                const uint32_t sa = smem_base + st * STAGE_BYTES;
                const uint32_t sb = sa + A_BYTES + rank * 16384;
                const int hpk = s2 * 4 + ((n2 + (kb >> 2)) & 3);
                const int kk = hpk * 256 + (kb & 3) * 64;
                tma_load_2d_mc(sb, &maps.wo[blk], n2 * 256 + rank * 128, kk, full_bar(st), 3);
                tma_load_2d_mc(sb + 8192, &maps.wo[blk], n2 * 256 + rank * 128 + 64, kk, full_bar(st), 3);
                if ((kb & 3) == 0) {
                    const int fi = (blk * 4 + m) * 16 + hpk;
                    unsigned int spins = 0;
                    while (ld_acquire(&g_oflag[fi]) < 2u) {
                        if (++spins > (1u << 26)) break;
                    }
                    if (atomicAdd(&g_ocons[fi], 1u) == 2u) {
                        g_ocons[fi] = 0u;
                        g_oflag[fi] = 0u;
                    }
                    fence_proxy_async();
                }
                tma_load_2d(sa, &maps.o, kk, blk * 512 + m * 128, full_bar(st));
                tma_load_2d(sa + 8192, &maps.o, kk, blk * 512 + m * 128 + 64, full_bar(st));
            }
        }
        __syncwarp();
        TL(9);
        asm volatile("barrier.cluster.arrive.release.aligned;\n\tbarrier.cluster.wait.acquire.aligned;" ::: "memory");
    } else {
        asm volatile("setmaxnreg.inc.sync.aligned.u32 232;");
        const int w = wg;
        const int wtid = tid & 127;
        const int warp = wtid >> 5, lane = tid & 31;
        int it = 0;
        auto release = [&](int st) {
            if (wtid == 0) {
                mbar_arrive(empty_bar(st));
                mbar_arrive_remote(empty_bar(st), rank ^ 1);
            }
        };
        auto mainloop = [&](float (&acc)[128], bool own_o) {
#pragma unroll
            for (int i = 0; i < 128; i++) acc[i] = 0.f;
            for (int kb = 0; kb < 16; kb++, it++) {
                const int st = it % STAGES;
                mbar_wait(full_bar(st), (it / STAGES) & 1);
                const uint32_t sa = (own_o && kb < 4) ? (kbuf + (w * 2 + (kb >> 1)) * 16384 + (kb & 1) * 8192)
                                                      : (smem_base + st * STAGE_BYTES + w * 8192);
                const uint32_t sb = smem_base + st * STAGE_BYTES + A_BYTES;
                wgmma_fence();
#pragma unroll
                for (int k = 0; k < 4; k++) {
                    wgmma_m64n256k16_ss(acc, make_desc(sa + k * 32, 16, 1024), make_desc(sb + k * 2048, 8192, 1024));
                }
                wgmma_commit();
                if (kb > 0) {
                    wgmma_wait<1>();
                    release((it - 1) % STAGES);
                }
            }
            wgmma_wait<0>();
            release((it - 1) % STAGES);
        };

        float acc[128];
        mainloop(acc, false);
        TL(1);

        uint32_t qf[64];
#pragma unroll
        for (int i = 0; i < 64; i++) qf[i] = pack_bf16(acc[2 * i], acc[2 * i + 1]);
#pragma unroll
        for (int hh = 0; hh < 2; hh++, it++) {
            const int st = it % STAGES;
            {
                const uint32_t sk = kbuf + (w * 2 + hh) * 16384;
                const uint32_t sv = smem_base + st * STAGE_BYTES + A_BYTES + w * 16384;
                const uint32_t so = sk;
                mbar_wait(bar_base + 136u + 8u * hh, 0);
                float sc[32];
                wgmma_fence();
#pragma unroll
                for (int t = 0; t < 8; t++) {
                    const int g = hh * 16 + 2 * t;
                    wgmma_m64n64k16_rs(sc, qf[2 * g], qf[2 * g + 1], qf[2 * g + 2], qf[2 * g + 3],
                                       make_desc(sk + (t >> 2) * 8192 + (t & 3) * 32, 16, 1024), t > 0);
                }
                wgmma_commit();
                wgmma_wait<0>();
                const bool hi = warp >= 2;
                float v0[8], v1[8];
#pragma unroll
                for (int g = 0; g < 4; g++) {
                    v0[2 * g] = hi ? sc[(g + 4) * 4 + 0] : sc[g * 4 + 0];
                    v0[2 * g + 1] = hi ? sc[(g + 4) * 4 + 1] : sc[g * 4 + 1];
                    v1[2 * g] = hi ? sc[(g + 4) * 4 + 2] : sc[g * 4 + 2];
                    v1[2 * g + 1] = hi ? sc[(g + 4) * 4 + 3] : sc[g * 4 + 3];
                }
                float m0 = v0[0], m1 = v1[0];
#pragma unroll
                for (int i = 1; i < 8; i++) { m0 = fmaxf(m0, v0[i]); m1 = fmaxf(m1, v1[i]); }
                m0 = fmaxf(m0, __shfl_xor_sync(0xffffffffu, m0, 1));
                m0 = fmaxf(m0, __shfl_xor_sync(0xffffffffu, m0, 2));
                m1 = fmaxf(m1, __shfl_xor_sync(0xffffffffu, m1, 1));
                m1 = fmaxf(m1, __shfl_xor_sync(0xffffffffu, m1, 2));
                const float cs = 0.08838834764831845f * 1.4426950408889634f;
                float s0 = 0.f, s1 = 0.f;
#pragma unroll
                for (int i = 0; i < 8; i++) {
                    v0[i] = exp2f((v0[i] - m0) * cs); s0 += v0[i];
                    v1[i] = exp2f((v1[i] - m1) * cs); s1 += v1[i];
                }
                s0 += __shfl_xor_sync(0xffffffffu, s0, 1);
                s0 += __shfl_xor_sync(0xffffffffu, s0, 2);
                s1 += __shfl_xor_sync(0xffffffffu, s1, 1);
                s1 += __shfl_xor_sync(0xffffffffu, s1, 2);
                const float i0 = 1.f / s0, i1 = 1.f / s1;
                uint32_t pf[8];
#pragma unroll
                for (int t = 0; t < 2; t++) {
                    pf[4 * t + 0] = pack_bf16(v0[4 * t + 0] * i0, v0[4 * t + 1] * i0);
                    pf[4 * t + 1] = pack_bf16(v1[4 * t + 0] * i1, v1[4 * t + 1] * i1);
                    pf[4 * t + 2] = pack_bf16(v0[4 * t + 2] * i0, v0[4 * t + 3] * i0);
                    pf[4 * t + 3] = pack_bf16(v1[4 * t + 2] * i1, v1[4 * t + 3] * i1);
                }
                float oc[64];
                mbar_wait(full_bar(st), (it / STAGES) & 1);
                TL(12 + hh);
                wgmma_fence();
#pragma unroll
                for (int t = 0; t < 4; t++) {
                    const bool val = (t >> 1) == (hi ? 1 : 0);
                    const int tt = t & 1;
                    wgmma_m64n128k16_rs(oc, val ? pf[4 * tt + 0] : 0u, val ? pf[4 * tt + 1] : 0u, val ? pf[4 * tt + 2] : 0u, val ? pf[4 * tt + 3] : 0u,
                                        make_desc(sv + t * 2048, 8192, 1024), t > 0);
                }
                wgmma_commit();
                wgmma_wait<0>();
#pragma unroll
                for (int c = 0; c < 8; c++) {
                    const uint32_t r0 = pack_bf16(oc[8 * c + 0], oc[8 * c + 1]);
                    const uint32_t r1 = pack_bf16(oc[8 * c + 2], oc[8 * c + 3]);
                    const uint32_t r2 = pack_bf16(oc[8 * c + 4], oc[8 * c + 5]);
                    const uint32_t r3 = pack_bf16(oc[8 * c + 6], oc[8 * c + 7]);
                    const int row = warp * 16 + (lane & 7) + ((lane >> 3) & 1) * 8;
                    const int chunk = (c & 3) * 2 + (lane >> 4);
                    const uint32_t addr = so + (c >> 2) * 8192 + row * 128 + ((chunk ^ (row & 7)) << 4);
                    stmatrix_x4(addr, r0, r1, r2, r3);
                }
                fence_proxy_async_smem();
                asm volatile("bar.arrive %0, 160;" ::"r"(4 + w) : "memory");
                if (hh == 1) TL(11);
            }
            release(st);
            TL(2 + hh);
        }

        asm volatile("bar.sync %0, 128;" ::"r"(1 + w) : "memory");
        mainloop(acc, true);
        TL(6);

        {
            const int tile = (blk * 4 + m) * 4 + n2;
            float* base = g_part + (size_t)(tile * 4) * (128 * 256);
#pragma unroll
            for (int q = 0; q < 4; q++) {
                if (q != s2) {
                    float4* p = reinterpret_cast<float4*>(base + (size_t)s2 * (128 * 256)) + ((q * 2 + w) * 8) * 128 + wtid;
#pragma unroll
                    for (int i = 0; i < 8; i++)
                        p[i * 128] = make_float4(acc[q * 32 + 4 * i], acc[q * 32 + 4 * i + 1], acc[q * 32 + 4 * i + 2], acc[q * 32 + 4 * i + 3]);
                }
            }
            asm volatile("bar.sync 3, 256;" ::: "memory");
            TL(7);
            if (w == 0 && wtid == 0) {
                __threadfence();
                atomicAdd(&g_rflag[tile], 1u);
                unsigned int spins = 0;
                while (ld_acquire(&g_rflag[tile]) < 4u) {
                    if (++spins > (1u << 26)) break;
                }
                if (atomicAdd(&g_rcons[tile], 1u) == 3u) {
                    g_rcons[tile] = 0u;
                    g_rflag[tile] = 0u;
                }
            }
            asm volatile("bar.sync 3, 256;" ::: "memory");
            TL(8);
            float r[32];
#pragma unroll
            for (int q = 0; q < 4; q++) {
                if (q == s2) {
#pragma unroll
                    for (int i = 0; i < 32; i++) r[i] = acc[q * 32 + i];
                }
            }
#pragma unroll
            for (int sp = 0; sp < 4; sp++) {
                if (sp != s2) {
                    const float4* p = reinterpret_cast<const float4*>(base + (size_t)sp * (128 * 256)) + ((s2 * 2 + w) * 8) * 128 + wtid;
#pragma unroll
                    for (int i = 0; i < 8; i++) {
                        const float4 t = __ldcg(p + i * 128);
                        r[4 * i] += t.x; r[4 * i + 1] += t.y; r[4 * i + 2] += t.z; r[4 * i + 3] += t.w;
                    }
                }
            }
            const int row = m * 128 + w * 64 + warp * 16 + (lane >> 2);
            __nv_bfloat16* op = out + (size_t)row * 2048 + blk * 1024 + n2 * 256 + s2 * 64 + (lane & 3) * 2;
#pragma unroll
            for (int g = 0; g < 8; g++) {
                *reinterpret_cast<uint32_t*>(op + g * 8) = pack_bf16(r[4 * g], r[4 * g + 1]);
                *reinterpret_cast<uint32_t*>(op + 8 * 2048 + g * 8) = pack_bf16(r[4 * g + 2], r[4 * g + 3]);
            }
        }
        TL(9);
        asm volatile("barrier.cluster.arrive.release.aligned;\n\tbarrier.cluster.wait.acquire.aligned;" ::: "memory");
    }
}

typedef CUresult (*EncodeFn)(CUtensorMap*, CUtensorMapDataType, cuuint32_t, void*, const cuuint64_t*, const cuuint64_t*,
                             const cuuint32_t*, const cuuint32_t*, CUtensorMapInterleave, CUtensorMapSwizzle,
                             CUtensorMapL2promotion, CUtensorMapFloatOOBfill);

static void make_map(EncodeFn fn, CUtensorMap* map, const void* ptr, uint64_t rows, uint64_t cols, uint32_t box_rows) {
    cuuint64_t dims[2] = {cols, rows};
    cuuint64_t strides[1] = {cols * 2};
    cuuint32_t box[2] = {64, box_rows};
    cuuint32_t estr[2] = {1, 1};
    fn(map, CU_TENSOR_MAP_DATA_TYPE_BFLOAT16, 2, const_cast<void*>(ptr), dims, strides, box, estr,
       CU_TENSOR_MAP_INTERLEAVE_NONE, CU_TENSOR_MAP_SWIZZLE_128B, CU_TENSOR_MAP_L2_PROMOTION_L2_128B, CU_TENSOR_MAP_FLOAT_OOB_FILL_NONE);
}

extern "C" void kernel_launch(void* const* d_in, const int* in_sizes, int n_in, void* d_out, int out_size) {
    static Maps maps;
    static bool ready = false;
    static void* cached[11];
    bool same = ready;
    for (int i = 0; i < 10 && same; i++) same = (cached[i] == d_in[i]);
    if (!same) {
        void* fnp = nullptr;
        cudaDriverEntryPointQueryResult qres;
        cudaGetDriverEntryPoint("cuTensorMapEncodeTiled", &fnp, cudaEnableDefault, &qres);
        EncodeFn fn = (EncodeFn)fnp;
        void* optr = nullptr;
        cudaGetSymbolAddress(&optr, g_o);
        for (int b = 0; b < 2; b++) {
            make_map(fn, &maps.x[b], d_in[5 * b + 0], 512, 1024, 128);
            make_map(fn, &maps.k[b], d_in[5 * b + 1], 16384, 128, 32);
            make_map(fn, &maps.v[b], d_in[5 * b + 2], 16384, 128, 32);
            make_map(fn, &maps.wq[b], d_in[5 * b + 3], 1024, 4096, 64);
            make_map(fn, &maps.wo[b], d_in[5 * b + 4], 4096, 1024, 64);
        }
        make_map(fn, &maps.o, optr, 1024, 4096, 64);
        cudaFuncSetAttribute(mha2_fused_kernel, cudaFuncAttributeMaxDynamicSharedMemorySize, SMEM_BYTES);
        for (int i = 0; i < 10; i++) cached[i] = d_in[i];
        ready = true;
    }
    mha2_fused_kernel<<<128, 384, SMEM_BYTES>>>(maps,
        (const __nv_bfloat16*)d_in[1], (const __nv_bfloat16*)d_in[2],
        (const __nv_bfloat16*)d_in[6], (const __nv_bfloat16*)d_in[7],
        (__nv_bfloat16*)d_out);
}
```

```cpp
#include <cuda_runtime.h>
#include <cuda_bf16.h>
#include <cuda.h>
#include <stdint.h>

#define DEVINL __device__ __forceinline__
#define PF_ON 1

constexpr int STAGES = 3;
constexpr int A_BYTES = 16384;
constexpr int B_BYTES = 32768;
constexpr int STAGE_BYTES = A_BYTES + B_BYTES;
constexpr int KBUF_BYTES = 65536;
constexpr int SMEM_BYTES = STAGES * STAGE_BYTES + KBUF_BYTES + 1024 + 256;

struct Maps {
    CUtensorMap x[2];
    CUtensorMap wq[2];
    CUtensorMap k[2];
    CUtensorMap v[2];
    CUtensorMap wo[2];
    CUtensorMap o;
};

__device__ __nv_bfloat16 g_o[2 * 512 * 4096];
__device__ float g_part[128 * 128 * 256];
__device__ unsigned int g_oflag[128];
__device__ unsigned int g_ocons[128];
__device__ unsigned int g_rflag[32];
__device__ unsigned int g_rcons[32];

#define TL(i)
DEVINL uint32_t smem_u32(const void* p) { return (uint32_t)__cvta_generic_to_shared(p); }

DEVINL void mbar_init(uint32_t bar, uint32_t count) {
    asm volatile("mbarrier.init.shared::cta.b64 [%0], %1;" ::"r"(bar), "r"(count));
}
DEVINL void mbar_expect_tx(uint32_t bar, uint32_t bytes) {
    asm volatile("mbarrier.arrive.expect_tx.shared::cta.b64 _, [%0], %1;" ::"r"(bar), "r"(bytes) : "memory");
}
DEVINL void mbar_arrive(uint32_t bar) {
    asm volatile("mbarrier.arrive.shared::cta.b64 _, [%0];" ::"r"(bar) : "memory");
}
DEVINL void mbar_arrive_remote(uint32_t bar, uint32_t cta) {
    asm volatile(
        "{\n\t.reg .b32 ra;\n\t"
        "mapa.shared::cluster.u32 ra, %0, %1;\n\t"
        "mbarrier.arrive.shared::cluster.b64 _, [ra];\n\t}"
        ::"r"(bar), "r"(cta) : "memory");
}
DEVINL void mbar_wait(uint32_t bar, uint32_t parity) {
    asm volatile(
        "{\n\t.reg .pred p;\n\t"
        "WAIT_LOOP:\n\t"
        "mbarrier.try_wait.parity.shared::cta.b64 p, [%0], %1, 0x989680;\n\t"
        "@p bra DONE;\n\t"
        "bra WAIT_LOOP;\n\t"
        "DONE:\n\t}"
        ::"r"(bar), "r"(parity) : "memory");
}
DEVINL void mbar_wait_cluster(uint32_t bar, uint32_t parity) {
    asm volatile(
        "{\n\t.reg .pred p;\n\t"
        "WAIT_LOOP:\n\t"
        "mbarrier.try_wait.parity.shared::cta.b64 p, [%0], %1, 0x989680;\n\t"
        "@p bra DONE;\n\t"
        "bra WAIT_LOOP;\n\t"
        "DONE:\n\t}"
        ::"r"(bar), "r"(parity) : "memory");
}

DEVINL void tma_load_2d(uint32_t dst, const CUtensorMap* map, int c0, int c1, uint32_t bar) {
    asm volatile(
        "cp.async.bulk.tensor.2d.shared::cluster.global.mbarrier::complete_tx::bytes [%0], [%1, {%3, %4}], [%2];"
        ::"r"(dst), "l"(map), "r"(bar), "r"(c0), "r"(c1) : "memory");
}
DEVINL void tma_load_2d_mc(uint32_t dst, const CUtensorMap* map, int c0, int c1, uint32_t bar, uint16_t mask) {
    asm volatile(
        "cp.async.bulk.tensor.2d.shared::cluster.global.mbarrier::complete_tx::bytes.multicast::cluster [%0], [%1, {%3, %4}], [%2], %5;"
        ::"r"(dst), "l"(map), "r"(bar), "r"(c0), "r"(c1), "h"(mask) : "memory");
}
DEVINL void tma_store_2d(const CUtensorMap* map, uint32_t src, int c0, int c1) {
    asm volatile(
        "cp.async.bulk.tensor.2d.global.shared::cta.bulk_group [%0, {%2, %3}], [%1];"
        ::"l"(map), "r"(src), "r"(c0), "r"(c1) : "memory");
}
DEVINL void l2_prefetch(const void* p, uint32_t bytes) {
    asm volatile("cp.async.bulk.prefetch.L2.global [%0], %1;" ::"l"(p), "r"(bytes) : "memory");
}
DEVINL void tma_prefetch_2d(const CUtensorMap* map, int c0, int c1) {
    asm volatile("cp.async.bulk.prefetch.tensor.2d.L2.global [%0, {%1, %2}];" ::"l"(map), "r"(c0), "r"(c1) : "memory");
}
DEVINL void fence_proxy_async() { asm volatile("fence.proxy.async;" ::: "memory"); }
DEVINL void fence_proxy_async_smem() { asm volatile("fence.proxy.async.shared::cta;" ::: "memory"); }

DEVINL void wgmma_fence() { asm volatile("wgmma.fence.sync.aligned;" ::: "memory"); }
DEVINL void wgmma_commit() { asm volatile("wgmma.commit_group.sync.aligned;" ::: "memory"); }
template <int N> DEVINL void wgmma_wait() { asm volatile("wgmma.wait_group.sync.aligned %0;" ::"n"(N) : "memory"); }

DEVINL uint64_t make_desc(uint32_t addr, uint32_t lbo_bytes, uint32_t sbo_bytes) {
    uint64_t d = 0;
    d |= (uint64_t)((addr & 0x3FFFF) >> 4);
    d |= (uint64_t)((lbo_bytes >> 4) & 0x3FFF) << 16;
    d |= (uint64_t)((sbo_bytes >> 4) & 0x3FFF) << 32;
    d |= (uint64_t)1 << 62;
    return d;
}

#define R8(a, i) "+f"(a[i]), "+f"(a[i + 1]), "+f"(a[i + 2]), "+f"(a[i + 3]), "+f"(a[i + 4]), "+f"(a[i + 5]), "+f"(a[i + 6]), "+f"(a[i + 7])
#define R32(a, i) R8(a, i), R8(a, i + 8), R8(a, i + 16), R8(a, i + 24)

DEVINL void wgmma_m64n256k16_ss(float (&d)[128], uint64_t da, uint64_t db) {
    asm volatile(
        "wgmma.mma_async.sync.aligned.m64n256k16.f32.bf16.bf16 "
        "{%0,%1,%2,%3,%4,%5,%6,%7,%8,%9,%10,%11,%12,%13,%14,%15,%16,%17,%18,%19,%20,%21,%22,%23,%24,%25,%26,%27,%28,%29,%30,%31,"
        "%32,%33,%34,%35,%36,%37,%38,%39,%40,%41,%42,%43,%44,%45,%46,%47,%48,%49,%50,%51,%52,%53,%54,%55,%56,%57,%58,%59,%60,%61,%62,%63,"
        "%64,%65,%66,%67,%68,%69,%70,%71,%72,%73,%74,%75,%76,%77,%78,%79,%80,%81,%82,%83,%84,%85,%86,%87,%88,%89,%90,%91,%92,%93,%94,%95,"
        "%96,%97,%98,%99,%100,%101,%102,%103,%104,%105,%106,%107,%108,%109,%110,%111,%112,%113,%114,%115,%116,%117,%118,%119,%120,%121,%122,%123,%124,%125,%126,%127},"
        " %128, %129, 1, 1, 1, 0, 1;"
        : R32(d, 0), R32(d, 32), R32(d, 64), R32(d, 96)
        : "l"(da), "l"(db));
}
DEVINL void wgmma_m64n64k16_rs(float (&d)[32], uint32_t a0, uint32_t a1, uint32_t a2, uint32_t a3, uint64_t db, int scale_d) {
    asm volatile(
        "{\n\t.reg .pred p;\n\tsetp.ne.b32 p, %37, 0;\n\t"
        "wgmma.mma_async.sync.aligned.m64n64k16.f32.bf16.bf16 "
        "{%0,%1,%2,%3,%4,%5,%6,%7,%8,%9,%10,%11,%12,%13,%14,%15,%16,%17,%18,%19,%20,%21,%22,%23,%24,%25,%26,%27,%28,%29,%30,%31},"
        " {%32,%33,%34,%35}, %36, p, 1, 1, 0;\n\t}"
        : R32(d, 0)
        : "r"(a0), "r"(a1), "r"(a2), "r"(a3), "l"(db), "r"(scale_d));
}
DEVINL void wgmma_m64n128k16_rs(float (&d)[64], uint32_t a0, uint32_t a1, uint32_t a2, uint32_t a3, uint64_t db, int scale_d) {
    asm volatile(
        "{\n\t.reg .pred p;\n\tsetp.ne.b32 p, %69, 0;\n\t"
        "wgmma.mma_async.sync.aligned.m64n128k16.f32.bf16.bf16 "
        "{%0,%1,%2,%3,%4,%5,%6,%7,%8,%9,%10,%11,%12,%13,%14,%15,%16,%17,%18,%19,%20,%21,%22,%23,%24,%25,%26,%27,%28,%29,%30,%31,"
        "%32,%33,%34,%35,%36,%37,%38,%39,%40,%41,%42,%43,%44,%45,%46,%47,%48,%49,%50,%51,%52,%53,%54,%55,%56,%57,%58,%59,%60,%61,%62,%63},"
        " {%64,%65,%66,%67}, %68, p, 1, 1, 1;\n\t}"
        : R32(d, 0), R32(d, 32)
        : "r"(a0), "r"(a1), "r"(a2), "r"(a3), "l"(db), "r"(scale_d));
}

DEVINL uint32_t pack_bf16(float lo, float hi) {
    __nv_bfloat162 t = __floats2bfloat162_rn(lo, hi);
    return *reinterpret_cast<uint32_t*>(&t);
}
DEVINL void stmatrix_x4(uint32_t addr, uint32_t r0, uint32_t r1, uint32_t r2, uint32_t r3) {
    asm volatile("stmatrix.sync.aligned.m8n8.x4.shared.b16 [%0], {%1,%2,%3,%4};" ::"r"(addr), "r"(r0), "r"(r1), "r"(r2), "r"(r3) : "memory");
}
DEVINL unsigned int ld_acquire(const unsigned int* p) {
    unsigned int v;
    asm volatile("ld.acquire.gpu.global.u32 %0, [%1];" : "=r"(v) : "l"(p) : "memory");
    return v;
}

__global__ void __cluster_dims__(2, 1, 1) __launch_bounds__(384, 1)
mha2_fused_kernel(const __grid_constant__ Maps maps,
                  const __nv_bfloat16* __restrict__ kA, const __nv_bfloat16* __restrict__ vA,
                  const __nv_bfloat16* __restrict__ kB, const __nv_bfloat16* __restrict__ vB,
                  __nv_bfloat16* __restrict__ out)
{
    extern __shared__ uint8_t smem_raw[];
    const uint32_t smem_base = (smem_u32(smem_raw) + 1023u) & ~1023u;
    const uint32_t kbuf = smem_base + STAGES * STAGE_BYTES;
    const uint32_t bar_base = kbuf + KBUF_BYTES;
    auto full_bar = [&](int s) { return bar_base + 8u * s; };
    auto empty_bar = [&](int s) { return bar_base + 64u + 8u * s; };

    auto slot_of = [&](int it) { return it < 24 ? it % 3 : (it == 24 ? 3 : (it - 25) & 3); };
    const int tid = threadIdx.x;
    const int wg = tid >> 7;
    uint32_t rank;
    asm volatile("mov.u32 %0, %%cluster_ctarank;" : "=r"(rank));
    const int cl = blockIdx.x >> 1;
    const int blk = cl >> 5;
    const int mp = (cl >> 4) & 1;
    const int m = mp * 2 + (int)rank;
    const int hp = cl & 15;
    const int n2 = hp & 3;
    const int s2 = hp >> 2;

    if (tid == 0) {
        for (int s = 0; s < 4; s++) {
            mbar_init(full_bar(s), 1);
            mbar_init(empty_bar(s), 4);
        }
        mbar_init(bar_base + 128u, 4);
        mbar_init(bar_base + 136u, 1);
        mbar_init(bar_base + 144u, 1);
        asm volatile("fence.mbarrier_init.release.cluster;" ::: "memory");
    }
    __syncthreads();
    asm volatile("barrier.cluster.arrive.release.aligned;\n\tbarrier.cluster.wait.acquire.aligned;" ::: "memory");

    TL(0);
    if (wg == 2) {
        asm volatile("setmaxnreg.dec.sync.aligned.u32 40;");
        if (tid >= 288 && tid < 352) {
            const int hw = (tid - 288) >> 5;
            for (int hh = 0; hh < 2; hh++) {
                asm volatile("bar.sync %0, 160;" ::"r"(4 + hw) : "memory");
                if ((tid & 31) == 0) {
                    const uint32_t so = kbuf + (hw * 2 + hh) * 16384;
                    const int col = (hp * 2 + hh) * 128;
                    const int row = blk * 512 + m * 128 + hw * 64;
                    tma_store_2d(&maps.o, so, col, row);
                    tma_store_2d(&maps.o, so + 8192, col + 64, row);
                    asm volatile("cp.async.bulk.commit_group;" ::: "memory");
                }
            }
            if ((tid & 31) == 0) {
                asm volatile("cp.async.bulk.wait_group 0;" ::: "memory");
                mbar_arrive(bar_base + 128u);
                mbar_arrive_remote(bar_base + 128u, rank ^ 1);
                __threadfence();
                atomicAdd(&g_oflag[(blk * 4 + m) * 16 + hp], 1u);
            }
        }
        if (tid == 256) {
            int it = 0;
            uint32_t par = 0x8u;
            auto acquire = [&](uint32_t bytes) {
                const int st = slot_of(it);
                if (it == 24) mbar_wait(bar_base + 128u, 0);
                mbar_wait_cluster(empty_bar(st), ((par >> st) & 1u) ^ 1u);
                par ^= 1u << st;
                mbar_expect_tx(full_bar(st), bytes);
                return st;
            };
            const __nv_bfloat16* kp = blk ? kB : kA;
            const __nv_bfloat16* vp = blk ? vB : vA;
            for (int kb = 0; kb < 16; kb++, it++) {
                const int st = acquire(STAGE_BYTES);
                const uint32_t sa = smem_base + st * STAGE_BYTES;
                tma_load_2d(sa, &maps.x[blk], kb * 64, m * 128, full_bar(st));
                const uint32_t sb = sa + A_BYTES + rank * 16384;
                tma_load_2d_mc(sb, &maps.wq[blk], hp * 256 + rank * 128, kb * 64, full_bar(st), 3);
                tma_load_2d_mc(sb + 8192, &maps.wq[blk], hp * 256 + rank * 128 + 64, kb * 64, full_bar(st), 3);
                if (kb < 8) {
                    const int j = kb;
                    const int hh = j >> 2, bq = j & 3;
                    if (bq == 0) mbar_expect_tx(bar_base + 136u + 8u * hh, 32768);
                    const int row = ((m * 4 + bq) * 32 + hp * 2 + hh) * 32;
                    const uint32_t dk = kbuf + ((bq >> 1) * 2 + hh) * 16384 + (bq & 1) * 4096;
                    tma_load_2d(dk, &maps.k[blk], 0, row, bar_base + 136u + 8u * hh);
                    tma_load_2d(dk + 8192, &maps.k[blk], 64, row, bar_base + 136u + 8u * hh);
                } else if (PF_ON) {
                    const int j = kb - 8;
                    const __nv_bfloat16* p = vp + ((size_t)((m * 4 + (j & 3)) * 32 + hp * 2 + (j >> 2))) * 4096;
                    l2_prefetch(p, 8192);
                }
            }
            TL(1);
            auto pf_wo = [&](int kb) {
                const int kk = (s2 * 4 + ((n2 + (kb >> 2)) & 3)) * 256 + (kb & 3) * 64;
                tma_prefetch_2d(&maps.wo[blk], n2 * 256 + rank * 128, kk);
                tma_prefetch_2d(&maps.wo[blk], n2 * 256 + rank * 128 + 64, kk);
            };
            for (int hh = 0; hh < 2; hh++, it++) {
                const int st = acquire(32768);
                TL(10 + hh);
                const uint32_t sv = smem_base + st * STAGE_BYTES + A_BYTES;
                for (int bq = 0; bq < 4; bq++) {
                    const int row = ((m * 4 + bq) * 32 + hp * 2 + hh) * 32;
                    const uint32_t dv = sv + (bq >> 1) * 16384 + (bq & 1) * 4096;
                    tma_load_2d(dv, &maps.v[blk], 0, row, full_bar(st));
                    tma_load_2d(dv + 8192, &maps.v[blk], 64, row, full_bar(st));
                }
            }
            TL(2);
            for (int kb = 0; kb < 4; kb++, it++) {
                const int st = acquire(B_BYTES);
                const uint32_t sb = smem_base + st * STAGE_BYTES + A_BYTES + rank * 16384;
                const int kk = hp * 256 + kb * 64;
                tma_load_2d_mc(sb, &maps.wo[blk], n2 * 256 + rank * 128, kk, full_bar(st), 3);
                tma_load_2d_mc(sb + 8192, &maps.wo[blk], n2 * 256 + rank * 128 + 64, kk, full_bar(st), 3);
            }
            TL(3);
            for (int kb = 4; kb < 16; kb++, it++) {
                if (kb == 5) TL(5);
                if (kb == 9) TL(6);
                if (kb == 13) TL(7);
                const int st = acquire(STAGE_BYTES);
                const uint32_t sa = smem_base + st * STAGE_BYTES;
                const uint32_t sb = sa + A_BYTES + rank * 16384;
                const int hpk = s2 * 4 + ((n2 + (kb >> 2)) & 3);
                const int kk = hpk * 256 + (kb & 3) * 64;
                tma_load_2d_mc(sb, &maps.wo[blk], n2 * 256 + rank * 128, kk, full_bar(st), 3);
                tma_load_2d_mc(sb + 8192, &maps.wo[blk], n2 * 256 + rank * 128 + 64, kk, full_bar(st), 3);
                if ((kb & 3) == 0) {
                    const int fi = (blk * 4 + m) * 16 + hpk;
                    unsigned int spins = 0;
                    while (ld_acquire(&g_oflag[fi]) < 2u) {
                        if (++spins > (1u << 26)) break;
                    }
                    if (atomicAdd(&g_ocons[fi], 1u) == 2u) {
                        g_ocons[fi] = 0u;
                        g_oflag[fi] = 0u;
                    }
                    fence_proxy_async();
                }
                tma_load_2d(sa, &maps.o, kk, blk * 512 + m * 128, full_bar(st));
                tma_load_2d(sa + 8192, &maps.o, kk, blk * 512 + m * 128 + 64, full_bar(st));
            }
        }
        __syncwarp();
        TL(9);
        asm volatile("barrier.cluster.arrive.release.aligned;\n\tbarrier.cluster.wait.acquire.aligned;" ::: "memory");
    } else {
        asm volatile("setmaxnreg.inc.sync.aligned.u32 232;");
        const int w = wg;
        const int wtid = tid & 127;
        const int warp = wtid >> 5, lane = tid & 31;
        int it = 0;
        uint32_t par = 0u;
        auto wait_full = [&](int st) {
            mbar_wait(full_bar(st), (par >> st) & 1u);
            par ^= 1u << st;
        };
        auto release = [&](int st) {
            if (wtid == 0) {
                mbar_arrive(empty_bar(st));
                mbar_arrive_remote(empty_bar(st), rank ^ 1);
            }
        };
        auto mainloop = [&](float (&acc)[128], bool own_o) {
#pragma unroll
            for (int i = 0; i < 128; i++) acc[i] = 0.f;
            for (int kb = 0; kb < 16; kb++, it++) {
                const int st = slot_of(it);
                wait_full(st);
                const uint32_t sa = (own_o && kb < 4) ? (kbuf + (w * 2 + (kb >> 1)) * 16384 + (kb & 1) * 8192)
                                                      : (smem_base + st * STAGE_BYTES + w * 8192);
                const uint32_t sb = smem_base + st * STAGE_BYTES + A_BYTES;
                wgmma_fence();
#pragma unroll
                for (int k = 0; k < 4; k++) {
                    wgmma_m64n256k16_ss(acc, make_desc(sa + k * 32, 16, 1024), make_desc(sb + k * 2048, 8192, 1024));
                }
                wgmma_commit();
                if (kb > 0) {
                    wgmma_wait<1>();
                    release(slot_of(it - 1));
                    if (own_o && kb == 4) release(3);
                }
            }
            wgmma_wait<0>();
            release(slot_of(it - 1));
        };

        float acc[128];
        mainloop(acc, false);
        TL(1);

        uint32_t qf[64];
#pragma unroll
        for (int i = 0; i < 64; i++) qf[i] = pack_bf16(acc[2 * i], acc[2 * i + 1]);
#pragma unroll
        for (int hh = 0; hh < 2; hh++, it++) {
            const int st = slot_of(it);
            {
                const uint32_t sk = kbuf + (w * 2 + hh) * 16384;
                const uint32_t sv = smem_base + st * STAGE_BYTES + A_BYTES + w * 16384;
                const uint32_t so = sk;
                mbar_wait(bar_base + 136u + 8u * hh, 0);
                float sc[32];
                wgmma_fence();
#pragma unroll
                for (int t = 0; t < 8; t++) {
                    const int g = hh * 16 + 2 * t;
                    wgmma_m64n64k16_rs(sc, qf[2 * g], qf[2 * g + 1], qf[2 * g + 2], qf[2 * g + 3],
                                       make_desc(sk + (t >> 2) * 8192 + (t & 3) * 32, 16, 1024), t > 0);
                }
                wgmma_commit();
                wgmma_wait<0>();
                const bool hi = warp >= 2;
                float v0[8], v1[8];
#pragma unroll
                for (int g = 0; g < 4; g++) {
                    v0[2 * g] = hi ? sc[(g + 4) * 4 + 0] : sc[g * 4 + 0];
                    v0[2 * g + 1] = hi ? sc[(g + 4) * 4 + 1] : sc[g * 4 + 1];
                    v1[2 * g] = hi ? sc[(g + 4) * 4 + 2] : sc[g * 4 + 2];
                    v1[2 * g + 1] = hi ? sc[(g + 4) * 4 + 3] : sc[g * 4 + 3];
                }
                float m0 = v0[0], m1 = v1[0];
#pragma unroll
                for (int i = 1; i < 8; i++) { m0 = fmaxf(m0, v0[i]); m1 = fmaxf(m1, v1[i]); }
                m0 = fmaxf(m0, __shfl_xor_sync(0xffffffffu, m0, 1));
                m0 = fmaxf(m0, __shfl_xor_sync(0xffffffffu, m0, 2));
                m1 = fmaxf(m1, __shfl_xor_sync(0xffffffffu, m1, 1));
                m1 = fmaxf(m1, __shfl_xor_sync(0xffffffffu, m1, 2));
                const float cs = 0.08838834764831845f * 1.4426950408889634f;
                float s0 = 0.f, s1 = 0.f;
#pragma unroll
                for (int i = 0; i < 8; i++) {
                    v0[i] = exp2f((v0[i] - m0) * cs); s0 += v0[i];
                    v1[i] = exp2f((v1[i] - m1) * cs); s1 += v1[i];
                }
                s0 += __shfl_xor_sync(0xffffffffu, s0, 1);
                s0 += __shfl_xor_sync(0xffffffffu, s0, 2);
                s1 += __shfl_xor_sync(0xffffffffu, s1, 1);
                s1 += __shfl_xor_sync(0xffffffffu, s1, 2);
                const float i0 = 1.f / s0, i1 = 1.f / s1;
                uint32_t pf[8];
#pragma unroll
                for (int t = 0; t < 2; t++) {
                    pf[4 * t + 0] = pack_bf16(v0[4 * t + 0] * i0, v0[4 * t + 1] * i0);
                    pf[4 * t + 1] = pack_bf16(v1[4 * t + 0] * i1, v1[4 * t + 1] * i1);
                    pf[4 * t + 2] = pack_bf16(v0[4 * t + 2] * i0, v0[4 * t + 3] * i0);
                    pf[4 * t + 3] = pack_bf16(v1[4 * t + 2] * i1, v1[4 * t + 3] * i1);
                }
                float oc[64];
                wait_full(st);
                TL(12 + hh);
                wgmma_fence();
#pragma unroll
                for (int t = 0; t < 4; t++) {
                    const bool val = (t >> 1) == (hi ? 1 : 0);
                    const int tt = t & 1;
                    wgmma_m64n128k16_rs(oc, val ? pf[4 * tt + 0] : 0u, val ? pf[4 * tt + 1] : 0u, val ? pf[4 * tt + 2] : 0u, val ? pf[4 * tt + 3] : 0u,
                                        make_desc(sv + t * 2048, 8192, 1024), t > 0);
                }
                wgmma_commit();
                wgmma_wait<0>();
#pragma unroll
                for (int c = 0; c < 8; c++) {
                    const uint32_t r0 = pack_bf16(oc[8 * c + 0], oc[8 * c + 1]);
                    const uint32_t r1 = pack_bf16(oc[8 * c + 2], oc[8 * c + 3]);
                    const uint32_t r2 = pack_bf16(oc[8 * c + 4], oc[8 * c + 5]);
                    const uint32_t r3 = pack_bf16(oc[8 * c + 6], oc[8 * c + 7]);
                    const int row = warp * 16 + (lane & 7) + ((lane >> 3) & 1) * 8;
                    const int chunk = (c & 3) * 2 + (lane >> 4);
                    const uint32_t addr = so + (c >> 2) * 8192 + row * 128 + ((chunk ^ (row & 7)) << 4);
                    stmatrix_x4(addr, r0, r1, r2, r3);
                }
                fence_proxy_async_smem();
                asm volatile("bar.arrive %0, 160;" ::"r"(4 + w) : "memory");
                if (hh == 1) TL(11);
            }
            release(st);
            TL(2 + hh);
        }

        asm volatile("bar.sync %0, 128;" ::"r"(1 + w) : "memory");
        mainloop(acc, true);
        TL(6);

        {
            const int tile = (blk * 4 + m) * 4 + n2;
            float* base = g_part + (size_t)(tile * 4) * (128 * 256);
#pragma unroll
            for (int q = 0; q < 4; q++) {
                if (q != s2) {
                    float4* p = reinterpret_cast<float4*>(base + (size_t)s2 * (128 * 256)) + ((q * 2 + w) * 8) * 128 + wtid;
#pragma unroll
                    for (int i = 0; i < 8; i++)
                        p[i * 128] = make_float4(acc[q * 32 + 4 * i], acc[q * 32 + 4 * i + 1], acc[q * 32 + 4 * i + 2], acc[q * 32 + 4 * i + 3]);
                }
            }
            asm volatile("bar.sync 3, 256;" ::: "memory");
            TL(7);
            if (w == 0 && wtid == 0) {
                __threadfence();
                atomicAdd(&g_rflag[tile], 1u);
                unsigned int spins = 0;
                while (ld_acquire(&g_rflag[tile]) < 4u) {
                    if (++spins > (1u << 26)) break;
                }
                if (atomicAdd(&g_rcons[tile], 1u) == 3u) {
                    g_rcons[tile] = 0u;
                    g_rflag[tile] = 0u;
                }
            }
            asm volatile("bar.sync 3, 256;" ::: "memory");
            TL(8);
            float r[32];
#pragma unroll
            for (int q = 0; q < 4; q++) {
                if (q == s2) {
#pragma unroll
                    for (int i = 0; i < 32; i++) r[i] = acc[q * 32 + i];
                }
            }
#pragma unroll
            for (int sp = 0; sp < 4; sp++) {
                if (sp != s2) {
                    const float4* p = reinterpret_cast<const float4*>(base + (size_t)sp * (128 * 256)) + ((s2 * 2 + w) * 8) * 128 + wtid;
#pragma unroll
                    for (int i = 0; i < 8; i++) {
                        const float4 t = __ldcg(p + i * 128);
                        r[4 * i] += t.x; r[4 * i + 1] += t.y; r[4 * i + 2] += t.z; r[4 * i + 3] += t.w;
                    }
                }
            }
            const int row = m * 128 + w * 64 + warp * 16 + (lane >> 2);
            __nv_bfloat16* op = out + (size_t)row * 2048 + blk * 1024 + n2 * 256 + s2 * 64 + (lane & 3) * 2;
#pragma unroll
            for (int g = 0; g < 8; g++) {
                *reinterpret_cast<uint32_t*>(op + g * 8) = pack_bf16(r[4 * g], r[4 * g + 1]);
                *reinterpret_cast<uint32_t*>(op + 8 * 2048 + g * 8) = pack_bf16(r[4 * g + 2], r[4 * g + 3]);
            }
        }
        TL(9);
        asm volatile("barrier.cluster.arrive.release.aligned;\n\tbarrier.cluster.wait.acquire.aligned;" ::: "memory");
    }
}

typedef CUresult (*EncodeFn)(CUtensorMap*, CUtensorMapDataType, cuuint32_t, void*, const cuuint64_t*, const cuuint64_t*,
                             const cuuint32_t*, const cuuint32_t*, CUtensorMapInterleave, CUtensorMapSwizzle,
                             CUtensorMapL2promotion, CUtensorMapFloatOOBfill);

static void make_map(EncodeFn fn, CUtensorMap* map, const void* ptr, uint64_t rows, uint64_t cols, uint32_t box_rows) {
    cuuint64_t dims[2] = {cols, rows};
    cuuint64_t strides[1] = {cols * 2};
    cuuint32_t box[2] = {64, box_rows};
    cuuint32_t estr[2] = {1, 1};
    fn(map, CU_TENSOR_MAP_DATA_TYPE_BFLOAT16, 2, const_cast<void*>(ptr), dims, strides, box, estr,
       CU_TENSOR_MAP_INTERLEAVE_NONE, CU_TENSOR_MAP_SWIZZLE_128B, CU_TENSOR_MAP_L2_PROMOTION_L2_128B, CU_TENSOR_MAP_FLOAT_OOB_FILL_NONE);
}

static void kernel_launch_stream(void* const* d_in, const int* in_sizes, int n_in, void* d_out, int out_size, cudaStream_t stream) {
    static Maps maps;
    static bool ready = false;
    static void* cached[11];
    bool same = ready;
    for (int i = 0; i < 10 && same; i++) same = (cached[i] == d_in[i]);
    if (!same) {
        void* fnp = nullptr;
        cudaDriverEntryPointQueryResult qres;
        cudaGetDriverEntryPoint("cuTensorMapEncodeTiled", &fnp, cudaEnableDefault, &qres);
        EncodeFn fn = (EncodeFn)fnp;
        void* optr = nullptr;
        cudaGetSymbolAddress(&optr, g_o);
        for (int b = 0; b < 2; b++) {
            make_map(fn, &maps.x[b], d_in[5 * b + 0], 512, 1024, 128);
            make_map(fn, &maps.k[b], d_in[5 * b + 1], 16384, 128, 32);
            make_map(fn, &maps.v[b], d_in[5 * b + 2], 16384, 128, 32);
            make_map(fn, &maps.wq[b], d_in[5 * b + 3], 1024, 4096, 64);
            make_map(fn, &maps.wo[b], d_in[5 * b + 4], 4096, 1024, 64);
        }
        make_map(fn, &maps.o, optr, 1024, 4096, 64);
        cudaFuncSetAttribute(mha2_fused_kernel, cudaFuncAttributeMaxDynamicSharedMemorySize, SMEM_BYTES);
        for (int i = 0; i < 10; i++) cached[i] = d_in[i];
        ready = true;
    }
    mha2_fused_kernel<<<128, 384, SMEM_BYTES, stream>>>(maps,
        (const __nv_bfloat16*)d_in[1], (const __nv_bfloat16*)d_in[2],
        (const __nv_bfloat16*)d_in[6], (const __nv_bfloat16*)d_in[7],
        (__nv_bfloat16*)d_out);
}

extern "C" void kernel_launch(void* const* d_in, const int* in_sizes, int n_in, void* d_out, int out_size) {
    kernel_launch_stream(d_in, in_sizes, n_in, d_out, out_size, (cudaStream_t)0);
}
```

```cpp
#include <cuda_runtime.h>
#include <cuda_bf16.h>
#include <cuda.h>
#include <stdint.h>

#define DEVINL __device__ __forceinline__
#define PF_ON 1

constexpr int STAGES = 3;
constexpr int A_BYTES = 16384;
constexpr int B_BYTES = 32768;
constexpr int STAGE_BYTES = A_BYTES + B_BYTES;
constexpr int KBUF_BYTES = 65536;
constexpr int SMEM_BYTES = STAGES * STAGE_BYTES + KBUF_BYTES + 1024 + 256;

struct Maps {
    CUtensorMap x[2];
    CUtensorMap wq[2];
    CUtensorMap k[2];
    CUtensorMap v[2];
    CUtensorMap wo[2];
    CUtensorMap o;
};

__device__ __nv_bfloat16 g_o[2 * 512 * 4096];
__device__ float g_part[128 * 128 * 256];
__device__ unsigned int g_oflag[128];
__device__ unsigned int g_ocons[128];
__device__ unsigned int g_rflag[32];
__device__ unsigned int g_rcons[32];

#define TL(i)
DEVINL uint32_t smem_u32(const void* p) { return (uint32_t)__cvta_generic_to_shared(p); }

DEVINL void mbar_init(uint32_t bar, uint32_t count) {
    asm volatile("mbarrier.init.shared::cta.b64 [%0], %1;" ::"r"(bar), "r"(count));
}
DEVINL void mbar_expect_tx(uint32_t bar, uint32_t bytes) {
    asm volatile("mbarrier.arrive.expect_tx.shared::cta.b64 _, [%0], %1;" ::"r"(bar), "r"(bytes) : "memory");
}
DEVINL void mbar_arrive(uint32_t bar) {
    asm volatile("mbarrier.arrive.shared::cta.b64 _, [%0];" ::"r"(bar) : "memory");
}
DEVINL void mbar_arrive_remote(uint32_t bar, uint32_t cta) {
    asm volatile(
        "{\n\t.reg .b32 ra;\n\t"
        "mapa.shared::cluster.u32 ra, %0, %1;\n\t"
        "mbarrier.arrive.shared::cluster.b64 _, [ra];\n\t}"
        ::"r"(bar), "r"(cta) : "memory");
}
DEVINL void mbar_wait(uint32_t bar, uint32_t parity) {
    asm volatile(
        "{\n\t.reg .pred p;\n\t"
        "WAIT_LOOP:\n\t"
        "mbarrier.try_wait.parity.shared::cta.b64 p, [%0], %1, 0x989680;\n\t"
        "@p bra DONE;\n\t"
        "bra WAIT_LOOP;\n\t"
        "DONE:\n\t}"
        ::"r"(bar), "r"(parity) : "memory");
}
DEVINL void mbar_wait_cluster(uint32_t bar, uint32_t parity) {
    asm volatile(
        "{\n\t.reg .pred p;\n\t"
        "WAIT_LOOP:\n\t"
        "mbarrier.try_wait.parity.shared::cta.b64 p, [%0], %1, 0x989680;\n\t"
        "@p bra DONE;\n\t"
        "bra WAIT_LOOP;\n\t"
        "DONE:\n\t}"
        ::"r"(bar), "r"(parity) : "memory");
}

DEVINL void tma_load_2d(uint32_t dst, const CUtensorMap* map, int c0, int c1, uint32_t bar) {
    asm volatile(
        "cp.async.bulk.tensor.2d.shared::cluster.global.mbarrier::complete_tx::bytes [%0], [%1, {%3, %4}], [%2];"
        ::"r"(dst), "l"(map), "r"(bar), "r"(c0), "r"(c1) : "memory");
}
DEVINL void tma_load_2d_mc(uint32_t dst, const CUtensorMap* map, int c0, int c1, uint32_t bar, uint16_t mask) {
    asm volatile(
        "cp.async.bulk.tensor.2d.shared::cluster.global.mbarrier::complete_tx::bytes.multicast::cluster [%0], [%1, {%3, %4}], [%2], %5;"
        ::"r"(dst), "l"(map), "r"(bar), "r"(c0), "r"(c1), "h"(mask) : "memory");
}
DEVINL void tma_store_2d(const CUtensorMap* map, uint32_t src, int c0, int c1) {
    asm volatile(
        "cp.async.bulk.tensor.2d.global.shared::cta.bulk_group [%0, {%2, %3}], [%1];"
        ::"l"(map), "r"(src), "r"(c0), "r"(c1) : "memory");
}
DEVINL void l2_prefetch(const void* p, uint32_t bytes) {
    asm volatile("cp.async.bulk.prefetch.L2.global [%0], %1;" ::"l"(p), "r"(bytes) : "memory");
}
DEVINL void tma_prefetch_2d(const CUtensorMap* map, int c0, int c1) {
    asm volatile("cp.async.bulk.prefetch.tensor.2d.L2.global [%0, {%1, %2}];" ::"l"(map), "r"(c0), "r"(c1) : "memory");
}
DEVINL void fence_proxy_async() { asm volatile("fence.proxy.async;" ::: "memory"); }
DEVINL void fence_proxy_async_smem() { asm volatile("fence.proxy.async.shared::cta;" ::: "memory"); }

DEVINL void wgmma_fence() { asm volatile("wgmma.fence.sync.aligned;" ::: "memory"); }
DEVINL void wgmma_commit() { asm volatile("wgmma.commit_group.sync.aligned;" ::: "memory"); }
template <int N> DEVINL void wgmma_wait() { asm volatile("wgmma.wait_group.sync.aligned %0;" ::"n"(N) : "memory"); }

DEVINL uint64_t make_desc(uint32_t addr, uint32_t lbo_bytes, uint32_t sbo_bytes) {
    uint64_t d = 0;
    d |= (uint64_t)((addr & 0x3FFFF) >> 4);
    d |= (uint64_t)((lbo_bytes >> 4) & 0x3FFF) << 16;
    d |= (uint64_t)((sbo_bytes >> 4) & 0x3FFF) << 32;
    d |= (uint64_t)1 << 62;
    return d;
}

#define R8(a, i) "+f"(a[i]), "+f"(a[i + 1]), "+f"(a[i + 2]), "+f"(a[i + 3]), "+f"(a[i + 4]), "+f"(a[i + 5]), "+f"(a[i + 6]), "+f"(a[i + 7])
#define R32(a, i) R8(a, i), R8(a, i + 8), R8(a, i + 16), R8(a, i + 24)

DEVINL void wgmma_m64n256k16_ss(float (&d)[128], uint64_t da, uint64_t db) {
    asm volatile(
        "wgmma.mma_async.sync.aligned.m64n256k16.f32.bf16.bf16 "
        "{%0,%1,%2,%3,%4,%5,%6,%7,%8,%9,%10,%11,%12,%13,%14,%15,%16,%17,%18,%19,%20,%21,%22,%23,%24,%25,%26,%27,%28,%29,%30,%31,"
        "%32,%33,%34,%35,%36,%37,%38,%39,%40,%41,%42,%43,%44,%45,%46,%47,%48,%49,%50,%51,%52,%53,%54,%55,%56,%57,%58,%59,%60,%61,%62,%63,"
        "%64,%65,%66,%67,%68,%69,%70,%71,%72,%73,%74,%75,%76,%77,%78,%79,%80,%81,%82,%83,%84,%85,%86,%87,%88,%89,%90,%91,%92,%93,%94,%95,"
        "%96,%97,%98,%99,%100,%101,%102,%103,%104,%105,%106,%107,%108,%109,%110,%111,%112,%113,%114,%115,%116,%117,%118,%119,%120,%121,%122,%123,%124,%125,%126,%127},"
        " %128, %129, 1, 1, 1, 0, 1;"
        : R32(d, 0), R32(d, 32), R32(d, 64), R32(d, 96)
        : "l"(da), "l"(db));
}
DEVINL void wgmma_m64n64k16_rs(float (&d)[32], uint32_t a0, uint32_t a1, uint32_t a2, uint32_t a3, uint64_t db, int scale_d) {
    asm volatile(
        "{\n\t.reg .pred p;\n\tsetp.ne.b32 p, %37, 0;\n\t"
        "wgmma.mma_async.sync.aligned.m64n64k16.f32.bf16.bf16 "
        "{%0,%1,%2,%3,%4,%5,%6,%7,%8,%9,%10,%11,%12,%13,%14,%15,%16,%17,%18,%19,%20,%21,%22,%23,%24,%25,%26,%27,%28,%29,%30,%31},"
        " {%32,%33,%34,%35}, %36, p, 1, 1, 0;\n\t}"
        : R32(d, 0)
        : "r"(a0), "r"(a1), "r"(a2), "r"(a3), "l"(db), "r"(scale_d));
}
DEVINL void wgmma_m64n128k16_rs(float (&d)[64], uint32_t a0, uint32_t a1, uint32_t a2, uint32_t a3, uint64_t db, int scale_d) {
    asm volatile(
        "{\n\t.reg .pred p;\n\tsetp.ne.b32 p, %69, 0;\n\t"
        "wgmma.mma_async.sync.aligned.m64n128k16.f32.bf16.bf16 "
        "{%0,%1,%2,%3,%4,%5,%6,%7,%8,%9,%10,%11,%12,%13,%14,%15,%16,%17,%18,%19,%20,%21,%22,%23,%24,%25,%26,%27,%28,%29,%30,%31,"
        "%32,%33,%34,%35,%36,%37,%38,%39,%40,%41,%42,%43,%44,%45,%46,%47,%48,%49,%50,%51,%52,%53,%54,%55,%56,%57,%58,%59,%60,%61,%62,%63},"
        " {%64,%65,%66,%67}, %68, p, 1, 1, 1;\n\t}"
        : R32(d, 0), R32(d, 32)
        : "r"(a0), "r"(a1), "r"(a2), "r"(a3), "l"(db), "r"(scale_d));
}

DEVINL uint32_t pack_bf16(float lo, float hi) {
    __nv_bfloat162 t = __floats2bfloat162_rn(lo, hi);
    return *reinterpret_cast<uint32_t*>(&t);
}
DEVINL void stmatrix_x4(uint32_t addr, uint32_t r0, uint32_t r1, uint32_t r2, uint32_t r3) {
    asm volatile("stmatrix.sync.aligned.m8n8.x4.shared.b16 [%0], {%1,%2,%3,%4};" ::"r"(addr), "r"(r0), "r"(r1), "r"(r2), "r"(r3) : "memory");
}
DEVINL unsigned int ld_acquire(const unsigned int* p) {
    unsigned int v;
    asm volatile("ld.acquire.gpu.global.u32 %0, [%1];" : "=r"(v) : "l"(p) : "memory");
    return v;
}

__global__ void __cluster_dims__(2, 1, 1) __launch_bounds__(384, 1)
mha2_fused_kernel(const __grid_constant__ Maps maps,
                  const __nv_bfloat16* __restrict__ kA, const __nv_bfloat16* __restrict__ vA,
                  const __nv_bfloat16* __restrict__ kB, const __nv_bfloat16* __restrict__ vB,
                  __nv_bfloat16* __restrict__ out)
{
    extern __shared__ uint8_t smem_raw[];
    const uint32_t smem_base = (smem_u32(smem_raw) + 1023u) & ~1023u;
    const uint32_t kbuf = smem_base + STAGES * STAGE_BYTES;
    const uint32_t bar_base = kbuf + KBUF_BYTES;
    auto full_bar = [&](int s) { return bar_base + 8u * s; };
    auto empty_bar = [&](int s) { return bar_base + 64u + 8u * s; };

    auto slot_of = [&](int it) { return it < 24 ? it % 3 : (it == 24 ? 3 : (it - 25) & 3); };
    const int tid = threadIdx.x;
    const int wg = tid >> 7;
    uint32_t rank;
    asm volatile("mov.u32 %0, %%cluster_ctarank;" : "=r"(rank));
    const int cl = blockIdx.x >> 1;
    const int blk = cl >> 5;
    const int mp = (cl >> 4) & 1;
    const int m = mp * 2 + (int)rank;
    const int hp = cl & 15;
    const int n2 = hp & 3;
    const int s2 = hp >> 2;

    if (tid == 0) {
        for (int s = 0; s < 4; s++) {
            mbar_init(full_bar(s), 1);
            mbar_init(empty_bar(s), 4);
        }
        mbar_init(bar_base + 128u, 4);
        for (int i = 1; i < 4; i++) mbar_init(bar_base + 152u + 8u * i, 1);
        mbar_init(bar_base + 136u, 1);
        mbar_init(bar_base + 144u, 1);
        asm volatile("fence.mbarrier_init.release.cluster;" ::: "memory");
    }
    __syncthreads();
    asm volatile("barrier.cluster.arrive.release.aligned;\n\tbarrier.cluster.wait.acquire.aligned;" ::: "memory");

    TL(0);
    if (wg == 2) {
        asm volatile("setmaxnreg.dec.sync.aligned.u32 40;");
        if (tid >= 288 && tid < 352) {
            const int hw = (tid - 288) >> 5;
            for (int hh = 0; hh < 2; hh++) {
                asm volatile("bar.sync %0, 160;" ::"r"(4 + hw) : "memory");
                if ((tid & 31) == 0) {
                    const uint32_t so = kbuf + (hw * 2 + hh) * 16384;
                    const int col = (hp * 2 + hh) * 128;
                    const int row = blk * 512 + m * 128 + hw * 64;
                    tma_store_2d(&maps.o, so, col, row);
                    tma_store_2d(&maps.o, so + 8192, col + 64, row);
                    asm volatile("cp.async.bulk.commit_group;" ::: "memory");
                }
            }
            if ((tid & 31) == 0) {
                asm volatile("cp.async.bulk.wait_group 0;" ::: "memory");
                mbar_arrive(bar_base + 128u);
                mbar_arrive_remote(bar_base + 128u, rank ^ 1);
                __threadfence();
                atomicAdd(&g_oflag[(blk * 4 + m) * 16 + hp], 1u);
            }
        }
        if (tid == 352) {
            for (int i = 1; i < 4; i++) {
                const int fi = (blk * 4 + m) * 16 + s2 * 4 + ((n2 + i) & 3);
                unsigned int spins = 0;
                while (ld_acquire(&g_oflag[fi]) < 2u) {
                    if (++spins > (1u << 26)) break;
                }
                mbar_arrive(bar_base + 152u + 8u * i);
                if (atomicAdd(&g_ocons[fi], 1u) == 2u) {
                    g_ocons[fi] = 0u;
                    g_oflag[fi] = 0u;
                }
            }
        }
        if (tid == 256) {
            int it = 0;
            uint32_t par = 0x8u;
            auto acquire = [&](uint32_t bytes) {
                const int st = slot_of(it);
                if (it == 24) mbar_wait(bar_base + 128u, 0);
                mbar_wait_cluster(empty_bar(st), ((par >> st) & 1u) ^ 1u);
                par ^= 1u << st;
                mbar_expect_tx(full_bar(st), bytes);
                return st;
            };
            const __nv_bfloat16* kp = blk ? kB : kA;
            const __nv_bfloat16* vp = blk ? vB : vA;
            for (int kb = 0; kb < 16; kb++, it++) {
                const int st = acquire(STAGE_BYTES);
                const uint32_t sa = smem_base + st * STAGE_BYTES;
                tma_load_2d(sa, &maps.x[blk], kb * 64, m * 128, full_bar(st));
                const uint32_t sb = sa + A_BYTES + rank * 16384;
                tma_load_2d_mc(sb, &maps.wq[blk], hp * 256 + rank * 128, kb * 64, full_bar(st), 3);
                tma_load_2d_mc(sb + 8192, &maps.wq[blk], hp * 256 + rank * 128 + 64, kb * 64, full_bar(st), 3);
                if (kb < 8) {
                    const int j = kb;
                    const int hh = j >> 2, bq = j & 3;
                    if (bq == 0) mbar_expect_tx(bar_base + 136u + 8u * hh, 32768);
                    const int row = ((m * 4 + bq) * 32 + hp * 2 + hh) * 32;
                    const uint32_t dk = kbuf + ((bq >> 1) * 2 + hh) * 16384 + (bq & 1) * 4096;
                    tma_load_2d(dk, &maps.k[blk], 0, row, bar_base + 136u + 8u * hh);
                    tma_load_2d(dk + 8192, &maps.k[blk], 64, row, bar_base + 136u + 8u * hh);
                } else if (PF_ON) {
                    const int j = kb - 8;
                    const __nv_bfloat16* p = vp + ((size_t)((m * 4 + (j & 3)) * 32 + hp * 2 + (j >> 2))) * 4096;
                    l2_prefetch(p, 8192);
                }
            }
            TL(1);
            auto pf_wo = [&](int kb) {
                const int kk = (s2 * 4 + ((n2 + (kb >> 2)) & 3)) * 256 + (kb & 3) * 64;
                tma_prefetch_2d(&maps.wo[blk], n2 * 256 + rank * 128, kk);
                tma_prefetch_2d(&maps.wo[blk], n2 * 256 + rank * 128 + 64, kk);
            };
            for (int hh = 0; hh < 2; hh++, it++) {
                const int st = acquire(32768);
                TL(10 + hh);
                const uint32_t sv = smem_base + st * STAGE_BYTES + A_BYTES;
                for (int bq = 0; bq < 4; bq++) {
                    const int row = ((m * 4 + bq) * 32 + hp * 2 + hh) * 32;
                    const uint32_t dv = sv + (bq >> 1) * 16384 + (bq & 1) * 4096;
                    tma_load_2d(dv, &maps.v[blk], 0, row, full_bar(st));
                    tma_load_2d(dv + 8192, &maps.v[blk], 64, row, full_bar(st));
                }
            }
            TL(2);
            for (int kb = 0; kb < 4; kb++, it++) {
                const int st = acquire(B_BYTES);
                const uint32_t sb = smem_base + st * STAGE_BYTES + A_BYTES + rank * 16384;
                const int kk = hp * 256 + kb * 64;
                tma_load_2d_mc(sb, &maps.wo[blk], n2 * 256 + rank * 128, kk, full_bar(st), 3);
                tma_load_2d_mc(sb + 8192, &maps.wo[blk], n2 * 256 + rank * 128 + 64, kk, full_bar(st), 3);
            }
            TL(3);
            for (int kb = 4; kb < 16; kb++, it++) {
                if (kb == 5) TL(5);
                if (kb == 9) TL(6);
                if (kb == 13) TL(7);
                const int st = acquire(STAGE_BYTES);
                const uint32_t sa = smem_base + st * STAGE_BYTES;
                const uint32_t sb = sa + A_BYTES + rank * 16384;
                const int hpk = s2 * 4 + ((n2 + (kb >> 2)) & 3);
                const int kk = hpk * 256 + (kb & 3) * 64;
                tma_load_2d_mc(sb, &maps.wo[blk], n2 * 256 + rank * 128, kk, full_bar(st), 3);
                tma_load_2d_mc(sb + 8192, &maps.wo[blk], n2 * 256 + rank * 128 + 64, kk, full_bar(st), 3);
                if ((kb & 3) == 0) {
                    mbar_wait(bar_base + 152u + 8u * (kb >> 2), 0);
                    fence_proxy_async();
                }
                tma_load_2d(sa, &maps.o, kk, blk * 512 + m * 128, full_bar(st));
                tma_load_2d(sa + 8192, &maps.o, kk, blk * 512 + m * 128 + 64, full_bar(st));
            }
        }
        __syncwarp();
        TL(9);
        asm volatile("barrier.cluster.arrive.release.aligned;\n\tbarrier.cluster.wait.acquire.aligned;" ::: "memory");
    } else {
        asm volatile("setmaxnreg.inc.sync.aligned.u32 232;");
        const int w = wg;
        const int wtid = tid & 127;
        const int warp = wtid >> 5, lane = tid & 31;
        int it = 0;
        uint32_t par = 0u;
        auto wait_full = [&](int st) {
            mbar_wait(full_bar(st), (par >> st) & 1u);
            par ^= 1u << st;
        };
        auto release = [&](int st) {
            if (wtid == 0) {
                mbar_arrive(empty_bar(st));
                mbar_arrive_remote(empty_bar(st), rank ^ 1);
            }
        };
        auto mainloop = [&](float (&acc)[128], bool own_o) {
#pragma unroll
            for (int i = 0; i < 128; i++) acc[i] = 0.f;
            for (int kb = 0; kb < 16; kb++, it++) {
                const int st = slot_of(it);
                wait_full(st);
                const uint32_t sa = (own_o && kb < 4) ? (kbuf + (w * 2 + (kb >> 1)) * 16384 + (kb & 1) * 8192)
                                                      : (smem_base + st * STAGE_BYTES + w * 8192);
                const uint32_t sb = smem_base + st * STAGE_BYTES + A_BYTES;
                wgmma_fence();
#pragma unroll
                for (int k = 0; k < 4; k++) {
                    wgmma_m64n256k16_ss(acc, make_desc(sa + k * 32, 16, 1024), make_desc(sb + k * 2048, 8192, 1024));
                }
                wgmma_commit();
                if (kb > 0) {
                    wgmma_wait<1>();
                    release(slot_of(it - 1));
                    if (own_o && kb == 4) release(3);
                }
            }
            wgmma_wait<0>();
            release(slot_of(it - 1));
        };

        float acc[128];
        mainloop(acc, false);
        TL(1);

        uint32_t qf[64];
#pragma unroll
        for (int i = 0; i < 64; i++) qf[i] = pack_bf16(acc[2 * i], acc[2 * i + 1]);
#pragma unroll
        for (int hh = 0; hh < 2; hh++, it++) {
            const int st = slot_of(it);
            {
                const uint32_t sk = kbuf + (w * 2 + hh) * 16384;
                const uint32_t sv = smem_base + st * STAGE_BYTES + A_BYTES + w * 16384;
                const uint32_t so = sk;
                mbar_wait(bar_base + 136u + 8u * hh, 0);
                float sc[32];
                wgmma_fence();
#pragma unroll
                for (int t = 0; t < 8; t++) {
                    const int g = hh * 16 + 2 * t;
                    wgmma_m64n64k16_rs(sc, qf[2 * g], qf[2 * g + 1], qf[2 * g + 2], qf[2 * g + 3],
                                       make_desc(sk + (t >> 2) * 8192 + (t & 3) * 32, 16, 1024), t > 0);
                }
                wgmma_commit();
                wgmma_wait<0>();
                const bool hi = warp >= 2;
                float v0[8], v1[8];
#pragma unroll
                for (int g = 0; g < 4; g++) {
                    v0[2 * g] = hi ? sc[(g + 4) * 4 + 0] : sc[g * 4 + 0];
                    v0[2 * g + 1] = hi ? sc[(g + 4) * 4 + 1] : sc[g * 4 + 1];
                    v1[2 * g] = hi ? sc[(g + 4) * 4 + 2] : sc[g * 4 + 2];
                    v1[2 * g + 1] = hi ? sc[(g + 4) * 4 + 3] : sc[g * 4 + 3];
                }
                float m0 = v0[0], m1 = v1[0];
#pragma unroll
                for (int i = 1; i < 8; i++) { m0 = fmaxf(m0, v0[i]); m1 = fmaxf(m1, v1[i]); }
                m0 = fmaxf(m0, __shfl_xor_sync(0xffffffffu, m0, 1));
                m0 = fmaxf(m0, __shfl_xor_sync(0xffffffffu, m0, 2));
                m1 = fmaxf(m1, __shfl_xor_sync(0xffffffffu, m1, 1));
                m1 = fmaxf(m1, __shfl_xor_sync(0xffffffffu, m1, 2));
                const float cs = 0.08838834764831845f * 1.4426950408889634f;
                float s0 = 0.f, s1 = 0.f;
#pragma unroll
                for (int i = 0; i < 8; i++) {
                    v0[i] = exp2f((v0[i] - m0) * cs); s0 += v0[i];
                    v1[i] = exp2f((v1[i] - m1) * cs); s1 += v1[i];
                }
                s0 += __shfl_xor_sync(0xffffffffu, s0, 1);
                s0 += __shfl_xor_sync(0xffffffffu, s0, 2);
                s1 += __shfl_xor_sync(0xffffffffu, s1, 1);
                s1 += __shfl_xor_sync(0xffffffffu, s1, 2);
                const float i0 = 1.f / s0, i1 = 1.f / s1;
                uint32_t pf[8];
#pragma unroll
                for (int t = 0; t < 2; t++) {
                    pf[4 * t + 0] = pack_bf16(v0[4 * t + 0] * i0, v0[4 * t + 1] * i0);
                    pf[4 * t + 1] = pack_bf16(v1[4 * t + 0] * i1, v1[4 * t + 1] * i1);
                    pf[4 * t + 2] = pack_bf16(v0[4 * t + 2] * i0, v0[4 * t + 3] * i0);
                    pf[4 * t + 3] = pack_bf16(v1[4 * t + 2] * i1, v1[4 * t + 3] * i1);
                }
                float oc[64];
                wait_full(st);
                TL(12 + hh);
                wgmma_fence();
#pragma unroll
                for (int t = 0; t < 4; t++) {
                    const bool val = (t >> 1) == (hi ? 1 : 0);
                    const int tt = t & 1;
                    wgmma_m64n128k16_rs(oc, val ? pf[4 * tt + 0] : 0u, val ? pf[4 * tt + 1] : 0u, val ? pf[4 * tt + 2] : 0u, val ? pf[4 * tt + 3] : 0u,
                                        make_desc(sv + t * 2048, 8192, 1024), t > 0);
                }
                wgmma_commit();
                wgmma_wait<0>();
#pragma unroll
                for (int c = 0; c < 8; c++) {
                    const uint32_t r0 = pack_bf16(oc[8 * c + 0], oc[8 * c + 1]);
                    const uint32_t r1 = pack_bf16(oc[8 * c + 2], oc[8 * c + 3]);
                    const uint32_t r2 = pack_bf16(oc[8 * c + 4], oc[8 * c + 5]);
                    const uint32_t r3 = pack_bf16(oc[8 * c + 6], oc[8 * c + 7]);
                    const int row = warp * 16 + (lane & 7) + ((lane >> 3) & 1) * 8;
                    const int chunk = (c & 3) * 2 + (lane >> 4);
                    const uint32_t addr = so + (c >> 2) * 8192 + row * 128 + ((chunk ^ (row & 7)) << 4);
                    stmatrix_x4(addr, r0, r1, r2, r3);
                }
                fence_proxy_async_smem();
                asm volatile("bar.arrive %0, 160;" ::"r"(4 + w) : "memory");
                if (hh == 1) TL(11);
            }
            release(st);
            TL(2 + hh);
        }

        asm volatile("bar.sync %0, 128;" ::"r"(1 + w) : "memory");
        mainloop(acc, true);
        TL(6);

        {
            const int tile = (blk * 4 + m) * 4 + n2;
            float* base = g_part + (size_t)(tile * 4) * (128 * 256);
#pragma unroll
            for (int q = 0; q < 4; q++) {
                if (q != s2) {
                    float4* p = reinterpret_cast<float4*>(base + (size_t)s2 * (128 * 256)) + ((q * 2 + w) * 8) * 128 + wtid;
#pragma unroll
                    for (int i = 0; i < 8; i++)
                        p[i * 128] = make_float4(acc[q * 32 + 4 * i], acc[q * 32 + 4 * i + 1], acc[q * 32 + 4 * i + 2], acc[q * 32 + 4 * i + 3]);
                }
            }
            asm volatile("bar.sync 3, 256;" ::: "memory");
            TL(7);
            if (w == 0 && wtid == 0) {
                __threadfence();
                atomicAdd(&g_rflag[tile], 1u);
                unsigned int spins = 0;
                while (ld_acquire(&g_rflag[tile]) < 4u) {
                    if (++spins > (1u << 26)) break;
                }
                if (atomicAdd(&g_rcons[tile], 1u) == 3u) {
                    g_rcons[tile] = 0u;
                    g_rflag[tile] = 0u;
                }
            }
            asm volatile("bar.sync 3, 256;" ::: "memory");
            TL(8);
            float r[32];
#pragma unroll
            for (int q = 0; q < 4; q++) {
                if (q == s2) {
#pragma unroll
                    for (int i = 0; i < 32; i++) r[i] = acc[q * 32 + i];
                }
            }
#pragma unroll
            for (int sp = 0; sp < 4; sp++) {
                if (sp != s2) {
                    const float4* p = reinterpret_cast<const float4*>(base + (size_t)sp * (128 * 256)) + ((s2 * 2 + w) * 8) * 128 + wtid;
#pragma unroll
                    for (int i = 0; i < 8; i++) {
                        const float4 t = __ldcg(p + i * 128);
                        r[4 * i] += t.x; r[4 * i + 1] += t.y; r[4 * i + 2] += t.z; r[4 * i + 3] += t.w;
                    }
                }
            }
            const int row = m * 128 + w * 64 + warp * 16 + (lane >> 2);
            __nv_bfloat16* op = out + (size_t)row * 2048 + blk * 1024 + n2 * 256 + s2 * 64 + (lane & 3) * 2;
#pragma unroll
            for (int g = 0; g < 8; g++) {
                *reinterpret_cast<uint32_t*>(op + g * 8) = pack_bf16(r[4 * g], r[4 * g + 1]);
                *reinterpret_cast<uint32_t*>(op + 8 * 2048 + g * 8) = pack_bf16(r[4 * g + 2], r[4 * g + 3]);
            }
        }
        TL(9);
        asm volatile("barrier.cluster.arrive.release.aligned;\n\tbarrier.cluster.wait.acquire.aligned;" ::: "memory");
    }
}

typedef CUresult (*EncodeFn)(CUtensorMap*, CUtensorMapDataType, cuuint32_t, void*, const cuuint64_t*, const cuuint64_t*,
                             const cuuint32_t*, const cuuint32_t*, CUtensorMapInterleave, CUtensorMapSwizzle,
                             CUtensorMapL2promotion, CUtensorMapFloatOOBfill);

static void make_map(EncodeFn fn, CUtensorMap* map, const void* ptr, uint64_t rows, uint64_t cols, uint32_t box_rows) {
    cuuint64_t dims[2] = {cols, rows};
    cuuint64_t strides[1] = {cols * 2};
    cuuint32_t box[2] = {64, box_rows};
    cuuint32_t estr[2] = {1, 1};
    fn(map, CU_TENSOR_MAP_DATA_TYPE_BFLOAT16, 2, const_cast<void*>(ptr), dims, strides, box, estr,
       CU_TENSOR_MAP_INTERLEAVE_NONE, CU_TENSOR_MAP_SWIZZLE_128B, CU_TENSOR_MAP_L2_PROMOTION_L2_128B, CU_TENSOR_MAP_FLOAT_OOB_FILL_NONE);
}

static void kernel_launch_stream(void* const* d_in, const int* in_sizes, int n_in, void* d_out, int out_size, cudaStream_t stream) {
    static Maps maps;
    static bool ready = false;
    static void* cached[11];
    bool same = ready;
    for (int i = 0; i < 10 && same; i++) same = (cached[i] == d_in[i]);
    if (!same) {
        void* fnp = nullptr;
        cudaDriverEntryPointQueryResult qres;
        cudaGetDriverEntryPoint("cuTensorMapEncodeTiled", &fnp, cudaEnableDefault, &qres);
        EncodeFn fn = (EncodeFn)fnp;
        void* optr = nullptr;
        cudaGetSymbolAddress(&optr, g_o);
        for (int b = 0; b < 2; b++) {
            make_map(fn, &maps.x[b], d_in[5 * b + 0], 512, 1024, 128);
            make_map(fn, &maps.k[b], d_in[5 * b + 1], 16384, 128, 32);
            make_map(fn, &maps.v[b], d_in[5 * b + 2], 16384, 128, 32);
            make_map(fn, &maps.wq[b], d_in[5 * b + 3], 1024, 4096, 64);
            make_map(fn, &maps.wo[b], d_in[5 * b + 4], 4096, 1024, 64);
        }
        make_map(fn, &maps.o, optr, 1024, 4096, 64);
        cudaFuncSetAttribute(mha2_fused_kernel, cudaFuncAttributeMaxDynamicSharedMemorySize, SMEM_BYTES);
        for (int i = 0; i < 10; i++) cached[i] = d_in[i];
        ready = true;
    }
    mha2_fused_kernel<<<128, 384, SMEM_BYTES, stream>>>(maps,
        (const __nv_bfloat16*)d_in[1], (const __nv_bfloat16*)d_in[2],
        (const __nv_bfloat16*)d_in[6], (const __nv_bfloat16*)d_in[7],
        (__nv_bfloat16*)d_out);
}

extern "C" void kernel_launch(void* const* d_in, const int* in_sizes, int n_in, void* d_out, int out_size) {
    kernel_launch_stream(d_in, in_sizes, n_in, d_out, out_size, (cudaStream_t)0);
}
```

```cpp
#include <cuda_runtime.h>
#include <cuda_bf16.h>
#include <cuda.h>
#include <stdint.h>

#define DEVINL __device__ __forceinline__
#define PF_ON 1

constexpr int STAGES = 3;
constexpr int A_BYTES = 16384;
constexpr int B_BYTES = 32768;
constexpr int STAGE_BYTES = A_BYTES + B_BYTES;
constexpr int KBUF_BYTES = 65536;
constexpr int SMEM_BYTES = STAGES * STAGE_BYTES + KBUF_BYTES + 1024 + 256;

struct Maps {
    CUtensorMap x[2];
    CUtensorMap wq[2];
    CUtensorMap k[2];
    CUtensorMap v[2];
    CUtensorMap wo[2];
    CUtensorMap o;
};

__device__ __nv_bfloat16 g_o[2 * 512 * 4096];
__device__ float g_part[128 * 128 * 256];
__device__ unsigned int g_oflag[128];
__device__ unsigned int g_ocons[128];
__device__ unsigned int g_rflag[32];
__device__ unsigned int g_rcons[32];

#define TL(i)
DEVINL uint32_t smem_u32(const void* p) { return (uint32_t)__cvta_generic_to_shared(p); }

DEVINL void mbar_init(uint32_t bar, uint32_t count) {
    asm volatile("mbarrier.init.shared::cta.b64 [%0], %1;" ::"r"(bar), "r"(count));
}
DEVINL void mbar_expect_tx(uint32_t bar, uint32_t bytes) {
    asm volatile("mbarrier.arrive.expect_tx.shared::cta.b64 _, [%0], %1;" ::"r"(bar), "r"(bytes) : "memory");
}
DEVINL void mbar_arrive(uint32_t bar) {
    asm volatile("mbarrier.arrive.shared::cta.b64 _, [%0];" ::"r"(bar) : "memory");
}
DEVINL void mbar_arrive_remote(uint32_t bar, uint32_t cta) {
    asm volatile(
        "{\n\t.reg .b32 ra;\n\t"
        "mapa.shared::cluster.u32 ra, %0, %1;\n\t"
        "mbarrier.arrive.shared::cluster.b64 _, [ra];\n\t}"
        ::"r"(bar), "r"(cta) : "memory");
}
DEVINL void mbar_wait(uint32_t bar, uint32_t parity) {
    asm volatile(
        "{\n\t.reg .pred p;\n\t"
        "WAIT_LOOP:\n\t"
        "mbarrier.try_wait.parity.shared::cta.b64 p, [%0], %1, 0x989680;\n\t"
        "@p bra DONE;\n\t"
        "bra WAIT_LOOP;\n\t"
        "DONE:\n\t}"
        ::"r"(bar), "r"(parity) : "memory");
}
DEVINL void mbar_wait_cluster(uint32_t bar, uint32_t parity) {
    asm volatile(
        "{\n\t.reg .pred p;\n\t"
        "WAIT_LOOP:\n\t"
        "mbarrier.try_wait.parity.shared::cta.b64 p, [%0], %1, 0x989680;\n\t"
        "@p bra DONE;\n\t"
        "bra WAIT_LOOP;\n\t"
        "DONE:\n\t}"
        ::"r"(bar), "r"(parity) : "memory");
}

DEVINL void tma_load_2d(uint32_t dst, const CUtensorMap* map, int c0, int c1, uint32_t bar) {
    asm volatile(
        "cp.async.bulk.tensor.2d.shared::cluster.global.mbarrier::complete_tx::bytes [%0], [%1, {%3, %4}], [%2];"
        ::"r"(dst), "l"(map), "r"(bar), "r"(c0), "r"(c1) : "memory");
}
DEVINL void tma_load_2d_mc(uint32_t dst, const CUtensorMap* map, int c0, int c1, uint32_t bar, uint16_t mask) {
    asm volatile(
        "cp.async.bulk.tensor.2d.shared::cluster.global.mbarrier::complete_tx::bytes.multicast::cluster [%0], [%1, {%3, %4}], [%2], %5;"
        ::"r"(dst), "l"(map), "r"(bar), "r"(c0), "r"(c1), "h"(mask) : "memory");
}
DEVINL void tma_store_2d(const CUtensorMap* map, uint32_t src, int c0, int c1) {
    asm volatile(
        "cp.async.bulk.tensor.2d.global.shared::cta.bulk_group [%0, {%2, %3}], [%1];"
        ::"l"(map), "r"(src), "r"(c0), "r"(c1) : "memory");
}
DEVINL void l2_prefetch(const void* p, uint32_t bytes) {
    asm volatile("cp.async.bulk.prefetch.L2.global [%0], %1;" ::"l"(p), "r"(bytes) : "memory");
}
DEVINL void tma_prefetch_2d(const CUtensorMap* map, int c0, int c1) {
    asm volatile("cp.async.bulk.prefetch.tensor.2d.L2.global [%0, {%1, %2}];" ::"l"(map), "r"(c0), "r"(c1) : "memory");
}
DEVINL void fence_proxy_async() { asm volatile("fence.proxy.async;" ::: "memory"); }
DEVINL void fence_proxy_async_smem() { asm volatile("fence.proxy.async.shared::cta;" ::: "memory"); }

DEVINL void wgmma_fence() { asm volatile("wgmma.fence.sync.aligned;" ::: "memory"); }
DEVINL void wgmma_commit() { asm volatile("wgmma.commit_group.sync.aligned;" ::: "memory"); }
template <int N> DEVINL void wgmma_wait() { asm volatile("wgmma.wait_group.sync.aligned %0;" ::"n"(N) : "memory"); }

DEVINL uint64_t make_desc(uint32_t addr, uint32_t lbo_bytes, uint32_t sbo_bytes) {
    uint64_t d = 0;
    d |= (uint64_t)((addr & 0x3FFFF) >> 4);
    d |= (uint64_t)((lbo_bytes >> 4) & 0x3FFF) << 16;
    d |= (uint64_t)((sbo_bytes >> 4) & 0x3FFF) << 32;
    d |= (uint64_t)1 << 62;
    return d;
}

#define R8(a, i) "+f"(a[i]), "+f"(a[i + 1]), "+f"(a[i + 2]), "+f"(a[i + 3]), "+f"(a[i + 4]), "+f"(a[i + 5]), "+f"(a[i + 6]), "+f"(a[i + 7])
#define R32(a, i) R8(a, i), R8(a, i + 8), R8(a, i + 16), R8(a, i + 24)

DEVINL void wgmma_m64n256k16_ss(float (&d)[128], uint64_t da, uint64_t db) {
    asm volatile(
        "wgmma.mma_async.sync.aligned.m64n256k16.f32.bf16.bf16 "
        "{%0,%1,%2,%3,%4,%5,%6,%7,%8,%9,%10,%11,%12,%13,%14,%15,%16,%17,%18,%19,%20,%21,%22,%23,%24,%25,%26,%27,%28,%29,%30,%31,"
        "%32,%33,%34,%35,%36,%37,%38,%39,%40,%41,%42,%43,%44,%45,%46,%47,%48,%49,%50,%51,%52,%53,%54,%55,%56,%57,%58,%59,%60,%61,%62,%63,"
        "%64,%65,%66,%67,%68,%69,%70,%71,%72,%73,%74,%75,%76,%77,%78,%79,%80,%81,%82,%83,%84,%85,%86,%87,%88,%89,%90,%91,%92,%93,%94,%95,"
        "%96,%97,%98,%99,%100,%101,%102,%103,%104,%105,%106,%107,%108,%109,%110,%111,%112,%113,%114,%115,%116,%117,%118,%119,%120,%121,%122,%123,%124,%125,%126,%127},"
        " %128, %129, 1, 1, 1, 0, 1;"
        : R32(d, 0), R32(d, 32), R32(d, 64), R32(d, 96)
        : "l"(da), "l"(db));
}
DEVINL void wgmma_m64n64k16_rs(float (&d)[32], uint32_t a0, uint32_t a1, uint32_t a2, uint32_t a3, uint64_t db, int scale_d) {
    asm volatile(
        "{\n\t.reg .pred p;\n\tsetp.ne.b32 p, %37, 0;\n\t"
        "wgmma.mma_async.sync.aligned.m64n64k16.f32.bf16.bf16 "
        "{%0,%1,%2,%3,%4,%5,%6,%7,%8,%9,%10,%11,%12,%13,%14,%15,%16,%17,%18,%19,%20,%21,%22,%23,%24,%25,%26,%27,%28,%29,%30,%31},"
        " {%32,%33,%34,%35}, %36, p, 1, 1, 0;\n\t}"
        : R32(d, 0)
        : "r"(a0), "r"(a1), "r"(a2), "r"(a3), "l"(db), "r"(scale_d));
}
DEVINL void wgmma_m64n128k16_rs(float (&d)[64], uint32_t a0, uint32_t a1, uint32_t a2, uint32_t a3, uint64_t db, int scale_d) {
    asm volatile(
        "{\n\t.reg .pred p;\n\tsetp.ne.b32 p, %69, 0;\n\t"
        "wgmma.mma_async.sync.aligned.m64n128k16.f32.bf16.bf16 "
        "{%0,%1,%2,%3,%4,%5,%6,%7,%8,%9,%10,%11,%12,%13,%14,%15,%16,%17,%18,%19,%20,%21,%22,%23,%24,%25,%26,%27,%28,%29,%30,%31,"
        "%32,%33,%34,%35,%36,%37,%38,%39,%40,%41,%42,%43,%44,%45,%46,%47,%48,%49,%50,%51,%52,%53,%54,%55,%56,%57,%58,%59,%60,%61,%62,%63},"
        " {%64,%65,%66,%67}, %68, p, 1, 1, 1;\n\t}"
        : R32(d, 0), R32(d, 32)
        : "r"(a0), "r"(a1), "r"(a2), "r"(a3), "l"(db), "r"(scale_d));
}

DEVINL uint32_t pack_bf16(float lo, float hi) {
    __nv_bfloat162 t = __floats2bfloat162_rn(lo, hi);
    return *reinterpret_cast<uint32_t*>(&t);
}
DEVINL void stmatrix_x4(uint32_t addr, uint32_t r0, uint32_t r1, uint32_t r2, uint32_t r3) {
    asm volatile("stmatrix.sync.aligned.m8n8.x4.shared.b16 [%0], {%1,%2,%3,%4};" ::"r"(addr), "r"(r0), "r"(r1), "r"(r2), "r"(r3) : "memory");
}
constexpr uint32_t PART_MAGIC = 0x7FC00001u;
DEVINL uint4 ld_relaxed_v4(const uint4* p) {
    uint4 v;
    asm volatile("ld.relaxed.gpu.global.v4.u32 {%0,%1,%2,%3}, [%4];" : "=r"(v.x), "=r"(v.y), "=r"(v.z), "=r"(v.w) : "l"(p) : "memory");
    return v;
}
DEVINL void st_relaxed_v4(uint4* p, uint32_t a, uint32_t b, uint32_t c, uint32_t d) {
    asm volatile("st.relaxed.gpu.global.v4.u32 [%0], {%1,%2,%3,%4};" ::"l"(p), "r"(a), "r"(b), "r"(c), "r"(d) : "memory");
}
DEVINL unsigned int ld_acquire(const unsigned int* p) {
    unsigned int v;
    asm volatile("ld.acquire.gpu.global.u32 %0, [%1];" : "=r"(v) : "l"(p) : "memory");
    return v;
}

__global__ void __cluster_dims__(2, 1, 1) __launch_bounds__(384, 1)
mha2_fused_kernel(const __grid_constant__ Maps maps,
                  const __nv_bfloat16* __restrict__ kA, const __nv_bfloat16* __restrict__ vA,
                  const __nv_bfloat16* __restrict__ kB, const __nv_bfloat16* __restrict__ vB,
                  __nv_bfloat16* __restrict__ out)
{
    extern __shared__ uint8_t smem_raw[];
    const uint32_t smem_base = (smem_u32(smem_raw) + 1023u) & ~1023u;
    const uint32_t kbuf = smem_base + STAGES * STAGE_BYTES;
    const uint32_t bar_base = kbuf + KBUF_BYTES;
    auto full_bar = [&](int s) { return bar_base + 8u * s; };
    auto empty_bar = [&](int s) { return bar_base + 64u + 8u * s; };

    auto slot_of = [&](int it) { return it < 24 ? it % 3 : (it == 24 ? 3 : (it - 25) & 3); };
    const int tid = threadIdx.x;
    const int wg = tid >> 7;
    uint32_t rank;
    asm volatile("mov.u32 %0, %%cluster_ctarank;" : "=r"(rank));
    const int cl = blockIdx.x >> 1;
    const int blk = cl >> 5;
    const int mp = (cl >> 4) & 1;
    const int m = mp * 2 + (int)rank;
    const int hp = cl & 15;
    const int n2 = hp & 3;
    const int s2 = hp >> 2;

    if (tid == 0) {
        for (int s = 0; s < 4; s++) {
            mbar_init(full_bar(s), 1);
            mbar_init(empty_bar(s), 4);
        }
        mbar_init(bar_base + 128u, 4);
        for (int i = 1; i < 4; i++) mbar_init(bar_base + 152u + 8u * i, 1);
        mbar_init(bar_base + 136u, 1);
        mbar_init(bar_base + 144u, 1);
        asm volatile("fence.mbarrier_init.release.cluster;" ::: "memory");
    }
    __syncthreads();
    asm volatile("barrier.cluster.arrive.release.aligned;\n\tbarrier.cluster.wait.acquire.aligned;" ::: "memory");

    TL(0);
    if (wg == 2) {
        asm volatile("setmaxnreg.dec.sync.aligned.u32 40;");
        if (tid >= 288 && tid < 352) {
            const int hw = (tid - 288) >> 5;
            for (int hh = 0; hh < 2; hh++) {
                asm volatile("bar.sync %0, 160;" ::"r"(4 + hw) : "memory");
                if ((tid & 31) == 0) {
                    const uint32_t so = kbuf + (hw * 2 + hh) * 16384;
                    const int col = (hp * 2 + hh) * 128;
                    const int row = blk * 512 + m * 128 + hw * 64;
                    tma_store_2d(&maps.o, so, col, row);
                    tma_store_2d(&maps.o, so + 8192, col + 64, row);
                    asm volatile("cp.async.bulk.commit_group;" ::: "memory");
                }
            }
            if ((tid & 31) == 0) {
                asm volatile("cp.async.bulk.wait_group 0;" ::: "memory");
                mbar_arrive(bar_base + 128u);
                mbar_arrive_remote(bar_base + 128u, rank ^ 1);
                __threadfence();
                atomicAdd(&g_oflag[(blk * 4 + m) * 16 + hp], 1u);
            }
        }
        if (tid == 352) {
            for (int i = 1; i < 4; i++) {
                const int fi = (blk * 4 + m) * 16 + s2 * 4 + ((n2 + i) & 3);
                unsigned int spins = 0;
                while (ld_acquire(&g_oflag[fi]) < 2u) {
                    if (++spins > (1u << 26)) break;
                }
                mbar_arrive(bar_base + 152u + 8u * i);
                if (atomicAdd(&g_ocons[fi], 1u) == 2u) {
                    g_ocons[fi] = 0u;
                    g_oflag[fi] = 0u;
                }
            }
        }
        if (tid == 256) {
            int it = 0;
            uint32_t par = 0x8u;
            auto acquire = [&](uint32_t bytes) {
                const int st = slot_of(it);
                if (it == 24) mbar_wait(bar_base + 128u, 0);
                mbar_wait_cluster(empty_bar(st), ((par >> st) & 1u) ^ 1u);
                par ^= 1u << st;
                mbar_expect_tx(full_bar(st), bytes);
                return st;
            };
            const __nv_bfloat16* kp = blk ? kB : kA;
            const __nv_bfloat16* vp = blk ? vB : vA;
            for (int kb = 0; kb < 16; kb++, it++) {
                const int st = acquire(STAGE_BYTES);
                const uint32_t sa = smem_base + st * STAGE_BYTES;
                tma_load_2d(sa, &maps.x[blk], kb * 64, m * 128, full_bar(st));
                const uint32_t sb = sa + A_BYTES + rank * 16384;
                tma_load_2d_mc(sb, &maps.wq[blk], hp * 256 + rank * 128, kb * 64, full_bar(st), 3);
                tma_load_2d_mc(sb + 8192, &maps.wq[blk], hp * 256 + rank * 128 + 64, kb * 64, full_bar(st), 3);
                if (kb < 8) {
                    const int j = kb;
                    const int hh = j >> 2, bq = j & 3;
                    if (bq == 0) mbar_expect_tx(bar_base + 136u + 8u * hh, 32768);
                    const int row = ((m * 4 + bq) * 32 + hp * 2 + hh) * 32;
                    const uint32_t dk = kbuf + ((bq >> 1) * 2 + hh) * 16384 + (bq & 1) * 4096;
                    tma_load_2d(dk, &maps.k[blk], 0, row, bar_base + 136u + 8u * hh);
                    tma_load_2d(dk + 8192, &maps.k[blk], 64, row, bar_base + 136u + 8u * hh);
                } else if (PF_ON) {
                    const int j = kb - 8;
                    const __nv_bfloat16* p = vp + ((size_t)((m * 4 + (j & 3)) * 32 + hp * 2 + (j >> 2))) * 4096;
                    l2_prefetch(p, 8192);
                }
            }
            TL(1);
            auto pf_wo = [&](int kb) {
                const int kk = (s2 * 4 + ((n2 + (kb >> 2)) & 3)) * 256 + (kb & 3) * 64;
                tma_prefetch_2d(&maps.wo[blk], n2 * 256 + rank * 128, kk);
                tma_prefetch_2d(&maps.wo[blk], n2 * 256 + rank * 128 + 64, kk);
            };
            for (int hh = 0; hh < 2; hh++, it++) {
                const int st = acquire(32768);
                TL(10 + hh);
                const uint32_t sv = smem_base + st * STAGE_BYTES + A_BYTES;
                for (int bq = 0; bq < 4; bq++) {
                    const int row = ((m * 4 + bq) * 32 + hp * 2 + hh) * 32;
                    const uint32_t dv = sv + (bq >> 1) * 16384 + (bq & 1) * 4096;
                    tma_load_2d(dv, &maps.v[blk], 0, row, full_bar(st));
                    tma_load_2d(dv + 8192, &maps.v[blk], 64, row, full_bar(st));
                }
            }
            TL(2);
            for (int kb = 0; kb < 4; kb++, it++) {
                const int st = acquire(B_BYTES);
                const uint32_t sb = smem_base + st * STAGE_BYTES + A_BYTES + rank * 16384;
                const int kk = hp * 256 + kb * 64;
                tma_load_2d_mc(sb, &maps.wo[blk], n2 * 256 + rank * 128, kk, full_bar(st), 3);
                tma_load_2d_mc(sb + 8192, &maps.wo[blk], n2 * 256 + rank * 128 + 64, kk, full_bar(st), 3);
            }
            TL(3);
            for (int kb = 4; kb < 16; kb++, it++) {
                if (kb == 5) TL(5);
                if (kb == 9) TL(6);
                if (kb == 13) TL(7);
                const int st = acquire(STAGE_BYTES);
                const uint32_t sa = smem_base + st * STAGE_BYTES;
                const uint32_t sb = sa + A_BYTES + rank * 16384;
                const int hpk = s2 * 4 + ((n2 + (kb >> 2)) & 3);
                const int kk = hpk * 256 + (kb & 3) * 64;
                tma_load_2d_mc(sb, &maps.wo[blk], n2 * 256 + rank * 128, kk, full_bar(st), 3);
                tma_load_2d_mc(sb + 8192, &maps.wo[blk], n2 * 256 + rank * 128 + 64, kk, full_bar(st), 3);
                if ((kb & 3) == 0) {
                    mbar_wait(bar_base + 152u + 8u * (kb >> 2), 0);
                    fence_proxy_async();
                }
                tma_load_2d(sa, &maps.o, kk, blk * 512 + m * 128, full_bar(st));
                tma_load_2d(sa + 8192, &maps.o, kk, blk * 512 + m * 128 + 64, full_bar(st));
            }
        }
        __syncwarp();
        TL(9);
        asm volatile("barrier.cluster.arrive.release.aligned;\n\tbarrier.cluster.wait.acquire.aligned;" ::: "memory");
    } else {
        asm volatile("setmaxnreg.inc.sync.aligned.u32 232;");
        const int w = wg;
        const int wtid = tid & 127;
        const int warp = wtid >> 5, lane = tid & 31;
        int it = 0;
        uint32_t par = 0u;
        auto wait_full = [&](int st) {
            mbar_wait(full_bar(st), (par >> st) & 1u);
            par ^= 1u << st;
        };
        auto release = [&](int st) {
            if (wtid == 0) {
                mbar_arrive(empty_bar(st));
                mbar_arrive_remote(empty_bar(st), rank ^ 1);
            }
        };
        auto mainloop = [&](float (&acc)[128], bool own_o) {
#pragma unroll
            for (int i = 0; i < 128; i++) acc[i] = 0.f;
            for (int kb = 0; kb < 16; kb++, it++) {
                const int st = slot_of(it);
                wait_full(st);
                const uint32_t sa = (own_o && kb < 4) ? (kbuf + (w * 2 + (kb >> 1)) * 16384 + (kb & 1) * 8192)
                                                      : (smem_base + st * STAGE_BYTES + w * 8192);
                const uint32_t sb = smem_base + st * STAGE_BYTES + A_BYTES;
                wgmma_fence();
#pragma unroll
                for (int k = 0; k < 4; k++) {
                    wgmma_m64n256k16_ss(acc, make_desc(sa + k * 32, 16, 1024), make_desc(sb + k * 2048, 8192, 1024));
                }
                wgmma_commit();
                if (kb > 0) {
                    wgmma_wait<1>();
                    release(slot_of(it - 1));
                    if (own_o && kb == 4) release(3);
                }
            }
            wgmma_wait<0>();
            release(slot_of(it - 1));
        };

        float acc[128];
        mainloop(acc, false);
        TL(1);

        uint32_t qf[64];
#pragma unroll
        for (int i = 0; i < 64; i++) qf[i] = pack_bf16(acc[2 * i], acc[2 * i + 1]);
#pragma unroll
        for (int hh = 0; hh < 2; hh++, it++) {
            const int st = slot_of(it);
            {
                const uint32_t sk = kbuf + (w * 2 + hh) * 16384;
                const uint32_t sv = smem_base + st * STAGE_BYTES + A_BYTES + w * 16384;
                const uint32_t so = sk;
                mbar_wait(bar_base + 136u + 8u * hh, 0);
                float sc[32];
                wgmma_fence();
#pragma unroll
                for (int t = 0; t < 8; t++) {
                    const int g = hh * 16 + 2 * t;
                    wgmma_m64n64k16_rs(sc, qf[2 * g], qf[2 * g + 1], qf[2 * g + 2], qf[2 * g + 3],
                                       make_desc(sk + (t >> 2) * 8192 + (t & 3) * 32, 16, 1024), t > 0);
                }
                wgmma_commit();
                wgmma_wait<0>();
                const bool hi = warp >= 2;
                float v0[8], v1[8];
#pragma unroll
                for (int g = 0; g < 4; g++) {
                    v0[2 * g] = hi ? sc[(g + 4) * 4 + 0] : sc[g * 4 + 0];
                    v0[2 * g + 1] = hi ? sc[(g + 4) * 4 + 1] : sc[g * 4 + 1];
                    v1[2 * g] = hi ? sc[(g + 4) * 4 + 2] : sc[g * 4 + 2];
                    v1[2 * g + 1] = hi ? sc[(g + 4) * 4 + 3] : sc[g * 4 + 3];
                }
                float m0 = v0[0], m1 = v1[0];
#pragma unroll
                for (int i = 1; i < 8; i++) { m0 = fmaxf(m0, v0[i]); m1 = fmaxf(m1, v1[i]); }
                m0 = fmaxf(m0, __shfl_xor_sync(0xffffffffu, m0, 1));
                m0 = fmaxf(m0, __shfl_xor_sync(0xffffffffu, m0, 2));
                m1 = fmaxf(m1, __shfl_xor_sync(0xffffffffu, m1, 1));
                m1 = fmaxf(m1, __shfl_xor_sync(0xffffffffu, m1, 2));
                const float cs = 0.08838834764831845f * 1.4426950408889634f;
                float s0 = 0.f, s1 = 0.f;
#pragma unroll
                for (int i = 0; i < 8; i++) {
                    v0[i] = exp2f((v0[i] - m0) * cs); s0 += v0[i];
                    v1[i] = exp2f((v1[i] - m1) * cs); s1 += v1[i];
                }
                s0 += __shfl_xor_sync(0xffffffffu, s0, 1);
                s0 += __shfl_xor_sync(0xffffffffu, s0, 2);
                s1 += __shfl_xor_sync(0xffffffffu, s1, 1);
                s1 += __shfl_xor_sync(0xffffffffu, s1, 2);
                const float i0 = 1.f / s0, i1 = 1.f / s1;
                uint32_t pf[8];
#pragma unroll
                for (int t = 0; t < 2; t++) {
                    pf[4 * t + 0] = pack_bf16(v0[4 * t + 0] * i0, v0[4 * t + 1] * i0);
                    pf[4 * t + 1] = pack_bf16(v1[4 * t + 0] * i1, v1[4 * t + 1] * i1);
                    pf[4 * t + 2] = pack_bf16(v0[4 * t + 2] * i0, v0[4 * t + 3] * i0);
                    pf[4 * t + 3] = pack_bf16(v1[4 * t + 2] * i1, v1[4 * t + 3] * i1);
                }
                float oc[64];
                wait_full(st);
                TL(12 + hh);
                wgmma_fence();
#pragma unroll
                for (int t = 0; t < 4; t++) {
                    const bool val = (t >> 1) == (hi ? 1 : 0);
                    const int tt = t & 1;
                    wgmma_m64n128k16_rs(oc, val ? pf[4 * tt + 0] : 0u, val ? pf[4 * tt + 1] : 0u, val ? pf[4 * tt + 2] : 0u, val ? pf[4 * tt + 3] : 0u,
                                        make_desc(sv + t * 2048, 8192, 1024), t > 0);
                }
                wgmma_commit();
                wgmma_wait<0>();
#pragma unroll
                for (int c = 0; c < 8; c++) {
                    const uint32_t r0 = pack_bf16(oc[8 * c + 0], oc[8 * c + 1]);
                    const uint32_t r1 = pack_bf16(oc[8 * c + 2], oc[8 * c + 3]);
                    const uint32_t r2 = pack_bf16(oc[8 * c + 4], oc[8 * c + 5]);
                    const uint32_t r3 = pack_bf16(oc[8 * c + 6], oc[8 * c + 7]);
                    const int row = warp * 16 + (lane & 7) + ((lane >> 3) & 1) * 8;
                    const int chunk = (c & 3) * 2 + (lane >> 4);
                    const uint32_t addr = so + (c >> 2) * 8192 + row * 128 + ((chunk ^ (row & 7)) << 4);
                    stmatrix_x4(addr, r0, r1, r2, r3);
                }
                fence_proxy_async_smem();
                asm volatile("bar.arrive %0, 160;" ::"r"(4 + w) : "memory");
                if (hh == 1) TL(11);
            }
            release(st);
            TL(2 + hh);
        }

        asm volatile("bar.sync %0, 128;" ::"r"(1 + w) : "memory");
        mainloop(acc, true);
        TL(6);

        {
            const int tile = (blk * 4 + m) * 4 + n2;
            uint4* base = reinterpret_cast<uint4*>(g_part) + (size_t)(tile * 4) * (128 * 64);
#pragma unroll
            for (int q = 0; q < 4; q++) {
                if (q != s2) {
                    uint4* p = base + (size_t)s2 * (128 * 64) + ((q * 2 + w) * 8) * 128 + wtid;
#pragma unroll
                    for (int i = 0; i < 8; i++)
                        st_relaxed_v4(p + i * 128, __float_as_uint(acc[q * 32 + 4 * i]) ^ PART_MAGIC, __float_as_uint(acc[q * 32 + 4 * i + 1]) ^ PART_MAGIC,
                                      __float_as_uint(acc[q * 32 + 4 * i + 2]) ^ PART_MAGIC, __float_as_uint(acc[q * 32 + 4 * i + 3]) ^ PART_MAGIC);
                }
            }
            TL(7);
            float r[32];
#pragma unroll
            for (int q = 0; q < 4; q++) {
                if (q == s2) {
#pragma unroll
                    for (int i = 0; i < 32; i++) r[i] = acc[q * 32 + i];
                }
            }
#pragma unroll
            for (int sp = 0; sp < 4; sp++) {
                if (sp != s2) {
                    uint4* p = base + (size_t)sp * (128 * 64) + ((s2 * 2 + w) * 8) * 128 + wtid;
                    uint4 t[8];
#pragma unroll
                    for (int i = 0; i < 8; i++) t[i] = ld_relaxed_v4(p + i * 128);
#pragma unroll
                    for (int i = 0; i < 8; i++) {
                        unsigned int spins = 0;
                        while (t[i].x == 0u || t[i].y == 0u || t[i].z == 0u || t[i].w == 0u) {
                            if (++spins > (1u << 24)) break;
                            t[i] = ld_relaxed_v4(p + i * 128);
                        }
                        st_relaxed_v4(p + i * 128, 0u, 0u, 0u, 0u);
                        r[4 * i] += __uint_as_float(t[i].x ^ PART_MAGIC); r[4 * i + 1] += __uint_as_float(t[i].y ^ PART_MAGIC);
                        r[4 * i + 2] += __uint_as_float(t[i].z ^ PART_MAGIC); r[4 * i + 3] += __uint_as_float(t[i].w ^ PART_MAGIC);
                    }
                }
            }
            TL(8);
            const int row = m * 128 + w * 64 + warp * 16 + (lane >> 2);
            __nv_bfloat16* op = out + (size_t)row * 2048 + blk * 1024 + n2 * 256 + s2 * 64 + (lane & 3) * 2;
#pragma unroll
            for (int g = 0; g < 8; g++) {
                *reinterpret_cast<uint32_t*>(op + g * 8) = pack_bf16(r[4 * g], r[4 * g + 1]);
                *reinterpret_cast<uint32_t*>(op + 8 * 2048 + g * 8) = pack_bf16(r[4 * g + 2], r[4 * g + 3]);
            }
        }
        TL(9);
        asm volatile("barrier.cluster.arrive.release.aligned;\n\tbarrier.cluster.wait.acquire.aligned;" ::: "memory");
    }
}

typedef CUresult (*EncodeFn)(CUtensorMap*, CUtensorMapDataType, cuuint32_t, void*, const cuuint64_t*, const cuuint64_t*,
                             const cuuint32_t*, const cuuint32_t*, CUtensorMapInterleave, CUtensorMapSwizzle,
                             CUtensorMapL2promotion, CUtensorMapFloatOOBfill);

static void make_map(EncodeFn fn, CUtensorMap* map, const void* ptr, uint64_t rows, uint64_t cols, uint32_t box_rows) {
    cuuint64_t dims[2] = {cols, rows};
    cuuint64_t strides[1] = {cols * 2};
    cuuint32_t box[2] = {64, box_rows};
    cuuint32_t estr[2] = {1, 1};
    fn(map, CU_TENSOR_MAP_DATA_TYPE_BFLOAT16, 2, const_cast<void*>(ptr), dims, strides, box, estr,
       CU_TENSOR_MAP_INTERLEAVE_NONE, CU_TENSOR_MAP_SWIZZLE_128B, CU_TENSOR_MAP_L2_PROMOTION_L2_128B, CU_TENSOR_MAP_FLOAT_OOB_FILL_NONE);
}

static void kernel_launch_stream(void* const* d_in, const int* in_sizes, int n_in, void* d_out, int out_size, cudaStream_t stream) {
    static Maps maps;
    static bool ready = false;
    static void* cached[11];
    bool same = ready;
    for (int i = 0; i < 10 && same; i++) same = (cached[i] == d_in[i]);
    if (!same) {
        void* fnp = nullptr;
        cudaDriverEntryPointQueryResult qres;
        cudaGetDriverEntryPoint("cuTensorMapEncodeTiled", &fnp, cudaEnableDefault, &qres);
        EncodeFn fn = (EncodeFn)fnp;
        void* optr = nullptr;
        cudaGetSymbolAddress(&optr, g_o);
        for (int b = 0; b < 2; b++) {
            make_map(fn, &maps.x[b], d_in[5 * b + 0], 512, 1024, 128);
            make_map(fn, &maps.k[b], d_in[5 * b + 1], 16384, 128, 32);
            make_map(fn, &maps.v[b], d_in[5 * b + 2], 16384, 128, 32);
            make_map(fn, &maps.wq[b], d_in[5 * b + 3], 1024, 4096, 64);
            make_map(fn, &maps.wo[b], d_in[5 * b + 4], 4096, 1024, 64);
        }
        make_map(fn, &maps.o, optr, 1024, 4096, 64);
        cudaFuncSetAttribute(mha2_fused_kernel, cudaFuncAttributeMaxDynamicSharedMemorySize, SMEM_BYTES);
        for (int i = 0; i < 10; i++) cached[i] = d_in[i];
        ready = true;
    }
    mha2_fused_kernel<<<128, 384, SMEM_BYTES, stream>>>(maps,
        (const __nv_bfloat16*)d_in[1], (const __nv_bfloat16*)d_in[2],
        (const __nv_bfloat16*)d_in[6], (const __nv_bfloat16*)d_in[7],
        (__nv_bfloat16*)d_out);
}

extern "C" void kernel_launch(void* const* d_in, const int* in_sizes, int n_in, void* d_out, int out_size) {
    kernel_launch_stream(d_in, in_sizes, n_in, d_out, out_size, (cudaStream_t)0);
}
```

```cpp
#include <cuda_runtime.h>
#include <cuda_bf16.h>
#include <cuda.h>
#include <stdint.h>

#define DEVINL __device__ __forceinline__
#define PF_ON 0

constexpr int STAGES = 3;
constexpr int A_BYTES = 16384;
constexpr int B_BYTES = 32768;
constexpr int STAGE_BYTES = A_BYTES + B_BYTES;
constexpr int KBUF_BYTES = 65536;
constexpr int SMEM_BYTES = STAGES * STAGE_BYTES + KBUF_BYTES + 1024 + 256;

struct Maps {
    CUtensorMap x[2];
    CUtensorMap wq[2];
    CUtensorMap k[2];
    CUtensorMap v[2];
    CUtensorMap wo[2];
    CUtensorMap o;
};

__device__ __nv_bfloat16 g_o[2 * 512 * 4096];
__device__ float g_part[128 * 128 * 256];
__device__ unsigned int g_oflag[128];
__device__ unsigned int g_ocons[128];
__device__ unsigned int g_rflag[32];
__device__ unsigned int g_rcons[32];

#define TL(i)
DEVINL uint32_t smem_u32(const void* p) { return (uint32_t)__cvta_generic_to_shared(p); }

DEVINL void mbar_init(uint32_t bar, uint32_t count) {
    asm volatile("mbarrier.init.shared::cta.b64 [%0], %1;" ::"r"(bar), "r"(count));
}
DEVINL void mbar_expect_tx(uint32_t bar, uint32_t bytes) {
    asm volatile("mbarrier.arrive.expect_tx.shared::cta.b64 _, [%0], %1;" ::"r"(bar), "r"(bytes) : "memory");
}
DEVINL void mbar_arrive(uint32_t bar) {
    asm volatile("mbarrier.arrive.shared::cta.b64 _, [%0];" ::"r"(bar) : "memory");
}
DEVINL void mbar_arrive_remote(uint32_t bar, uint32_t cta) {
    asm volatile(
        "{\n\t.reg .b32 ra;\n\t"
        "mapa.shared::cluster.u32 ra, %0, %1;\n\t"
        "mbarrier.arrive.shared::cluster.b64 _, [ra];\n\t}"
        ::"r"(bar), "r"(cta) : "memory");
}
DEVINL void mbar_wait(uint32_t bar, uint32_t parity) {
    asm volatile(
        "{\n\t.reg .pred p;\n\t"
        "WAIT_LOOP:\n\t"
        "mbarrier.try_wait.parity.shared::cta.b64 p, [%0], %1, 0x989680;\n\t"
        "@p bra DONE;\n\t"
        "bra WAIT_LOOP;\n\t"
        "DONE:\n\t}"
        ::"r"(bar), "r"(parity) : "memory");
}
DEVINL void mbar_wait_cluster(uint32_t bar, uint32_t parity) {
    asm volatile(
        "{\n\t.reg .pred p;\n\t"
        "WAIT_LOOP:\n\t"
        "mbarrier.try_wait.parity.shared::cta.b64 p, [%0], %1, 0x989680;\n\t"
        "@p bra DONE;\n\t"
        "bra WAIT_LOOP;\n\t"
        "DONE:\n\t}"
        ::"r"(bar), "r"(parity) : "memory");
}

DEVINL void tma_load_2d(uint32_t dst, const CUtensorMap* map, int c0, int c1, uint32_t bar) {
    asm volatile(
        "cp.async.bulk.tensor.2d.shared::cluster.global.mbarrier::complete_tx::bytes [%0], [%1, {%3, %4}], [%2];"
        ::"r"(dst), "l"(map), "r"(bar), "r"(c0), "r"(c1) : "memory");
}
DEVINL void tma_load_2d_mc(uint32_t dst, const CUtensorMap* map, int c0, int c1, uint32_t bar, uint16_t mask) {
    asm volatile(
        "cp.async.bulk.tensor.2d.shared::cluster.global.mbarrier::complete_tx::bytes.multicast::cluster [%0], [%1, {%3, %4}], [%2], %5;"
        ::"r"(dst), "l"(map), "r"(bar), "r"(c0), "r"(c1), "h"(mask) : "memory");
}
DEVINL void tma_store_2d(const CUtensorMap* map, uint32_t src, int c0, int c1) {
    asm volatile(
        "cp.async.bulk.tensor.2d.global.shared::cta.bulk_group [%0, {%2, %3}], [%1];"
        ::"l"(map), "r"(src), "r"(c0), "r"(c1) : "memory");
}
DEVINL void l2_prefetch(const void* p, uint32_t bytes) {
    asm volatile("cp.async.bulk.prefetch.L2.global [%0], %1;" ::"l"(p), "r"(bytes) : "memory");
}
DEVINL void tma_prefetch_2d(const CUtensorMap* map, int c0, int c1) {
    asm volatile("cp.async.bulk.prefetch.tensor.2d.L2.global [%0, {%1, %2}];" ::"l"(map), "r"(c0), "r"(c1) : "memory");
}
DEVINL void fence_proxy_async() { asm volatile("fence.proxy.async;" ::: "memory"); }
DEVINL void fence_proxy_async_smem() { asm volatile("fence.proxy.async.shared::cta;" ::: "memory"); }

DEVINL void wgmma_fence() { asm volatile("wgmma.fence.sync.aligned;" ::: "memory"); }
DEVINL void wgmma_commit() { asm volatile("wgmma.commit_group.sync.aligned;" ::: "memory"); }
template <int N> DEVINL void wgmma_wait() { asm volatile("wgmma.wait_group.sync.aligned %0;" ::"n"(N) : "memory"); }

DEVINL uint64_t make_desc(uint32_t addr, uint32_t lbo_bytes, uint32_t sbo_bytes) {
    uint64_t d = 0;
    d |= (uint64_t)((addr & 0x3FFFF) >> 4);
    d |= (uint64_t)((lbo_bytes >> 4) & 0x3FFF) << 16;
    d |= (uint64_t)((sbo_bytes >> 4) & 0x3FFF) << 32;
    d |= (uint64_t)1 << 62;
    return d;
}

#define R8(a, i) "+f"(a[i]), "+f"(a[i + 1]), "+f"(a[i + 2]), "+f"(a[i + 3]), "+f"(a[i + 4]), "+f"(a[i + 5]), "+f"(a[i + 6]), "+f"(a[i + 7])
#define R32(a, i) R8(a, i), R8(a, i + 8), R8(a, i + 16), R8(a, i + 24)

DEVINL void wgmma_m64n256k16_ss(float (&d)[128], uint64_t da, uint64_t db) {
    asm volatile(
        "wgmma.mma_async.sync.aligned.m64n256k16.f32.bf16.bf16 "
        "{%0,%1,%2,%3,%4,%5,%6,%7,%8,%9,%10,%11,%12,%13,%14,%15,%16,%17,%18,%19,%20,%21,%22,%23,%24,%25,%26,%27,%28,%29,%30,%31,"
        "%32,%33,%34,%35,%36,%37,%38,%39,%40,%41,%42,%43,%44,%45,%46,%47,%48,%49,%50,%51,%52,%53,%54,%55,%56,%57,%58,%59,%60,%61,%62,%63,"
        "%64,%65,%66,%67,%68,%69,%70,%71,%72,%73,%74,%75,%76,%77,%78,%79,%80,%81,%82,%83,%84,%85,%86,%87,%88,%89,%90,%91,%92,%93,%94,%95,"
        "%96,%97,%98,%99,%100,%101,%102,%103,%104,%105,%106,%107,%108,%109,%110,%111,%112,%113,%114,%115,%116,%117,%118,%119,%120,%121,%122,%123,%124,%125,%126,%127},"
        " %128, %129, 1, 1, 1, 0, 1;"
        : R32(d, 0), R32(d, 32), R32(d, 64), R32(d, 96)
        : "l"(da), "l"(db));
}
DEVINL void wgmma_m64n64k16_rs(float (&d)[32], uint32_t a0, uint32_t a1, uint32_t a2, uint32_t a3, uint64_t db, int scale_d) {
    asm volatile(
        "{\n\t.reg .pred p;\n\tsetp.ne.b32 p, %37, 0;\n\t"
        "wgmma.mma_async.sync.aligned.m64n64k16.f32.bf16.bf16 "
        "{%0,%1,%2,%3,%4,%5,%6,%7,%8,%9,%10,%11,%12,%13,%14,%15,%16,%17,%18,%19,%20,%21,%22,%23,%24,%25,%26,%27,%28,%29,%30,%31},"
        " {%32,%33,%34,%35}, %36, p, 1, 1, 0;\n\t}"
        : R32(d, 0)
        : "r"(a0), "r"(a1), "r"(a2), "r"(a3), "l"(db), "r"(scale_d));
}
DEVINL void wgmma_m64n128k16_rs(float (&d)[64], uint32_t a0, uint32_t a1, uint32_t a2, uint32_t a3, uint64_t db, int scale_d) {
    asm volatile(
        "{\n\t.reg .pred p;\n\tsetp.ne.b32 p, %69, 0;\n\t"
        "wgmma.mma_async.sync.aligned.m64n128k16.f32.bf16.bf16 "
        "{%0,%1,%2,%3,%4,%5,%6,%7,%8,%9,%10,%11,%12,%13,%14,%15,%16,%17,%18,%19,%20,%21,%22,%23,%24,%25,%26,%27,%28,%29,%30,%31,"
        "%32,%33,%34,%35,%36,%37,%38,%39,%40,%41,%42,%43,%44,%45,%46,%47,%48,%49,%50,%51,%52,%53,%54,%55,%56,%57,%58,%59,%60,%61,%62,%63},"
        " {%64,%65,%66,%67}, %68, p, 1, 1, 1;\n\t}"
        : R32(d, 0), R32(d, 32)
        : "r"(a0), "r"(a1), "r"(a2), "r"(a3), "l"(db), "r"(scale_d));
}

DEVINL uint32_t pack_bf16(float lo, float hi) {
    __nv_bfloat162 t = __floats2bfloat162_rn(lo, hi);
    return *reinterpret_cast<uint32_t*>(&t);
}
DEVINL float bf_lo(uint32_t u) { return __uint_as_float(u << 16); }
DEVINL float bf_hi(uint32_t u) { return __uint_as_float(u & 0xffff0000u); }
DEVINL void stmatrix_x4(uint32_t addr, uint32_t r0, uint32_t r1, uint32_t r2, uint32_t r3) {
    asm volatile("stmatrix.sync.aligned.m8n8.x4.shared.b16 [%0], {%1,%2,%3,%4};" ::"r"(addr), "r"(r0), "r"(r1), "r"(r2), "r"(r3) : "memory");
}
constexpr uint32_t PART_MAGIC = 0x7FC00001u;
DEVINL uint4 ld_relaxed_v4(const uint4* p) {
    uint4 v;
    asm volatile("ld.relaxed.gpu.global.v4.u32 {%0,%1,%2,%3}, [%4];" : "=r"(v.x), "=r"(v.y), "=r"(v.z), "=r"(v.w) : "l"(p) : "memory");
    return v;
}
DEVINL void st_relaxed_v4(uint4* p, uint32_t a, uint32_t b, uint32_t c, uint32_t d) {
    asm volatile("st.relaxed.gpu.global.v4.u32 [%0], {%1,%2,%3,%4};" ::"l"(p), "r"(a), "r"(b), "r"(c), "r"(d) : "memory");
}
DEVINL unsigned int ld_acquire(const unsigned int* p) {
    unsigned int v;
    asm volatile("ld.acquire.gpu.global.u32 %0, [%1];" : "=r"(v) : "l"(p) : "memory");
    return v;
}

__global__ void __cluster_dims__(2, 1, 1) __launch_bounds__(384, 1)
mha2_fused_kernel(const __grid_constant__ Maps maps,
                  const __nv_bfloat16* __restrict__ kA, const __nv_bfloat16* __restrict__ vA,
                  const __nv_bfloat16* __restrict__ kB, const __nv_bfloat16* __restrict__ vB,
                  __nv_bfloat16* __restrict__ out)
{
    extern __shared__ uint8_t smem_raw[];
    const uint32_t smem_base = (smem_u32(smem_raw) + 1023u) & ~1023u;
    const uint32_t kbuf = smem_base + STAGES * STAGE_BYTES;
    const uint32_t bar_base = kbuf + KBUF_BYTES;
    auto full_bar = [&](int s) { return bar_base + 8u * s; };
    auto empty_bar = [&](int s) { return bar_base + 64u + 8u * s; };

    auto slot_of = [&](int it) { return it < 24 ? it % 3 : (it == 24 ? 3 : (it - 25) & 3); };
    const int tid = threadIdx.x;
    const int wg = tid >> 7;
    uint32_t rank;
    asm volatile("mov.u32 %0, %%cluster_ctarank;" : "=r"(rank));
    const int cl = blockIdx.x >> 1;
    const int blk = cl >> 5;
    const int mp = (cl >> 4) & 1;
    const int m = mp * 2 + (int)rank;
    const int hp = cl & 15;
    const int n2 = hp & 3;
    const int s2 = hp >> 2;

    if (tid == 0) {
        for (int s = 0; s < 4; s++) {
            mbar_init(full_bar(s), 1);
            mbar_init(empty_bar(s), 4);
        }
        mbar_init(bar_base + 128u, 4);
        for (int i = 1; i < 4; i++) mbar_init(bar_base + 152u + 8u * i, 1);
        mbar_init(bar_base + 136u, 1);
        mbar_init(bar_base + 144u, 1);
        asm volatile("fence.mbarrier_init.release.cluster;" ::: "memory");
    }
    __syncthreads();
    asm volatile("barrier.cluster.arrive.release.aligned;\n\tbarrier.cluster.wait.acquire.aligned;" ::: "memory");

    TL(0);
    if (wg == 2) {
        asm volatile("setmaxnreg.dec.sync.aligned.u32 40;");
        if (tid >= 288 && tid < 352) {
            const int hw = (tid - 288) >> 5;
            for (int hh = 0; hh < 2; hh++) {
                asm volatile("bar.sync %0, 160;" ::"r"(4 + hw) : "memory");
                if ((tid & 31) == 0) {
                    const uint32_t so = kbuf + (hw * 2 + hh) * 16384;
                    const int col = (hp * 2 + hh) * 128;
                    const int row = blk * 512 + m * 128 + hw * 64;
                    tma_store_2d(&maps.o, so, col, row);
                    tma_store_2d(&maps.o, so + 8192, col + 64, row);
                    asm volatile("cp.async.bulk.commit_group;" ::: "memory");
                }
            }
            if ((tid & 31) == 0) {
                asm volatile("cp.async.bulk.wait_group 0;" ::: "memory");
                mbar_arrive(bar_base + 128u);
                mbar_arrive_remote(bar_base + 128u, rank ^ 1);
                __threadfence();
                atomicAdd(&g_oflag[(blk * 4 + m) * 16 + hp], 1u);
            }
        }
        if (tid == 352) {
            for (int i = 1; i < 4; i++) {
                const int fi = (blk * 4 + m) * 16 + s2 * 4 + ((n2 + i) & 3);
                unsigned int spins = 0;
                while (ld_acquire(&g_oflag[fi]) < 2u) {
                    if (++spins > (1u << 26)) break;
                }
                mbar_arrive(bar_base + 152u + 8u * i);
                if (atomicAdd(&g_ocons[fi], 1u) == 2u) {
                    g_ocons[fi] = 0u;
                    g_oflag[fi] = 0u;
                }
            }
        }
        if (tid == 256) {
            int it = 0;
            uint32_t par = 0x8u;
            auto acquire = [&](uint32_t bytes) {
                const int st = slot_of(it);
                if (it == 24) mbar_wait(bar_base + 128u, 0);
                mbar_wait_cluster(empty_bar(st), ((par >> st) & 1u) ^ 1u);
                par ^= 1u << st;
                mbar_expect_tx(full_bar(st), bytes);
                return st;
            };
            const __nv_bfloat16* kp = blk ? kB : kA;
            const __nv_bfloat16* vp = blk ? vB : vA;
            for (int kb = 0; kb < 16; kb++, it++) {
                const int st = acquire(STAGE_BYTES);
                const uint32_t sa = smem_base + st * STAGE_BYTES;
                tma_load_2d(sa, &maps.x[blk], kb * 64, m * 128, full_bar(st));
                const uint32_t sb = sa + A_BYTES + rank * 16384;
                tma_load_2d_mc(sb, &maps.wq[blk], hp * 256 + rank * 128, kb * 64, full_bar(st), 3);
                tma_load_2d_mc(sb + 8192, &maps.wq[blk], hp * 256 + rank * 128 + 64, kb * 64, full_bar(st), 3);
                if (kb < 8) {
                    const int j = kb;
                    const int hh = j >> 2, bq = j & 3;
                    if (bq == 0) mbar_expect_tx(bar_base + 136u + 8u * hh, 32768);
                    const int row = ((m * 4 + bq) * 32 + hp * 2 + hh) * 32;
                    const uint32_t dk = kbuf + ((bq >> 1) * 2 + hh) * 16384 + (bq & 1) * 4096;
                    tma_load_2d(dk, &maps.k[blk], 0, row, bar_base + 136u + 8u * hh);
                    tma_load_2d(dk + 8192, &maps.k[blk], 64, row, bar_base + 136u + 8u * hh);
                } else if (PF_ON) {
                    const int j = kb - 8;
                    const __nv_bfloat16* p = vp + ((size_t)((m * 4 + (j & 3)) * 32 + hp * 2 + (j >> 2))) * 4096;
                    l2_prefetch(p, 8192);
                }
            }
            TL(1);
            auto pf_wo = [&](int kb) {
                const int kk = (s2 * 4 + ((n2 + (kb >> 2)) & 3)) * 256 + (kb & 3) * 64;
                tma_prefetch_2d(&maps.wo[blk], n2 * 256 + rank * 128, kk);
                tma_prefetch_2d(&maps.wo[blk], n2 * 256 + rank * 128 + 64, kk);
            };
            for (int hh = 0; hh < 2; hh++, it++) {
                const int st = acquire(32768);
                TL(10 + hh);
                const uint32_t sv = smem_base + st * STAGE_BYTES + A_BYTES;
                for (int bq = 0; bq < 4; bq++) {
                    const int row = ((m * 4 + bq) * 32 + hp * 2 + hh) * 32;
                    const uint32_t dv = sv + (bq >> 1) * 16384 + (bq & 1) * 4096;
                    tma_load_2d(dv, &maps.v[blk], 0, row, full_bar(st));
                    tma_load_2d(dv + 8192, &maps.v[blk], 64, row, full_bar(st));
                }
            }
            TL(2);
            for (int kb = 0; kb < 4; kb++, it++) {
                const int st = acquire(B_BYTES);
                const uint32_t sb = smem_base + st * STAGE_BYTES + A_BYTES + rank * 16384;
                const int kk = hp * 256 + kb * 64;
                tma_load_2d_mc(sb, &maps.wo[blk], n2 * 256 + rank * 128, kk, full_bar(st), 3);
                tma_load_2d_mc(sb + 8192, &maps.wo[blk], n2 * 256 + rank * 128 + 64, kk, full_bar(st), 3);
            }
            TL(3);
            for (int kb = 4; kb < 16; kb++, it++) {
                if (kb == 5) TL(5);
                if (kb == 9) TL(6);
                if (kb == 13) TL(7);
                const int st = acquire(STAGE_BYTES);
                const uint32_t sa = smem_base + st * STAGE_BYTES;
                const uint32_t sb = sa + A_BYTES + rank * 16384;
                const int hpk = s2 * 4 + ((n2 + (kb >> 2)) & 3);
                const int kk = hpk * 256 + (kb & 3) * 64;
                tma_load_2d_mc(sb, &maps.wo[blk], n2 * 256 + rank * 128, kk, full_bar(st), 3);
                tma_load_2d_mc(sb + 8192, &maps.wo[blk], n2 * 256 + rank * 128 + 64, kk, full_bar(st), 3);
                if ((kb & 3) == 0) {
                    mbar_wait(bar_base + 152u + 8u * (kb >> 2), 0);
                    fence_proxy_async();
                }
                tma_load_2d(sa, &maps.o, kk, blk * 512 + m * 128, full_bar(st));
                tma_load_2d(sa + 8192, &maps.o, kk, blk * 512 + m * 128 + 64, full_bar(st));
            }
        }
        __syncwarp();
        TL(9);
        asm volatile("barrier.cluster.arrive.release.aligned;\n\tbarrier.cluster.wait.acquire.aligned;" ::: "memory");
    } else {
        asm volatile("setmaxnreg.inc.sync.aligned.u32 232;");
        const int w = wg;
        const int wtid = tid & 127;
        const int warp = wtid >> 5, lane = tid & 31;
        int it = 0;
        uint32_t par = 0u;
        auto wait_full = [&](int st) {
            mbar_wait(full_bar(st), (par >> st) & 1u);
            par ^= 1u << st;
        };
        auto release = [&](int st) {
            if (wtid == 0) {
                mbar_arrive(empty_bar(st));
                mbar_arrive_remote(empty_bar(st), rank ^ 1);
            }
        };
        auto mainloop = [&](float (&acc)[128], bool own_o) {
#pragma unroll
            for (int i = 0; i < 128; i++) acc[i] = 0.f;
            for (int kb = 0; kb < 16; kb++, it++) {
                const int st = slot_of(it);
                wait_full(st);
                const uint32_t sa = (own_o && kb < 4) ? (kbuf + (w * 2 + (kb >> 1)) * 16384 + (kb & 1) * 8192)
                                                      : (smem_base + st * STAGE_BYTES + w * 8192);
                const uint32_t sb = smem_base + st * STAGE_BYTES + A_BYTES;
                wgmma_fence();
#pragma unroll
                for (int k = 0; k < 4; k++) {
                    wgmma_m64n256k16_ss(acc, make_desc(sa + k * 32, 16, 1024), make_desc(sb + k * 2048, 8192, 1024));
                }
                wgmma_commit();
                if (kb > 0) {
                    wgmma_wait<1>();
                    release(slot_of(it - 1));
                    if (own_o && kb == 4) release(3);
                }
            }
            wgmma_wait<0>();
            release(slot_of(it - 1));
        };

        float acc[128];
        mainloop(acc, false);
        TL(1);

        uint32_t qf[64];
#pragma unroll
        for (int i = 0; i < 64; i++) qf[i] = pack_bf16(acc[2 * i], acc[2 * i + 1]);
#pragma unroll
        for (int hh = 0; hh < 2; hh++, it++) {
            const int st = slot_of(it);
            {
                const uint32_t sk = kbuf + (w * 2 + hh) * 16384;
                const uint32_t sv = smem_base + st * STAGE_BYTES + A_BYTES + w * 16384;
                const uint32_t so = sk;
                mbar_wait(bar_base + 136u + 8u * hh, 0);
                float sc[32];
                wgmma_fence();
#pragma unroll
                for (int t = 0; t < 8; t++) {
                    const int g = hh * 16 + 2 * t;
                    wgmma_m64n64k16_rs(sc, qf[2 * g], qf[2 * g + 1], qf[2 * g + 2], qf[2 * g + 3],
                                       make_desc(sk + (t >> 2) * 8192 + (t & 3) * 32, 16, 1024), t > 0);
                }
                wgmma_commit();
                wgmma_wait<0>();
                const bool hi = warp >= 2;
                float v0[8], v1[8];
#pragma unroll
                for (int g = 0; g < 4; g++) {
                    v0[2 * g] = hi ? sc[(g + 4) * 4 + 0] : sc[g * 4 + 0];
                    v0[2 * g + 1] = hi ? sc[(g + 4) * 4 + 1] : sc[g * 4 + 1];
                    v1[2 * g] = hi ? sc[(g + 4) * 4 + 2] : sc[g * 4 + 2];
                    v1[2 * g + 1] = hi ? sc[(g + 4) * 4 + 3] : sc[g * 4 + 3];
                }
                float m0 = v0[0], m1 = v1[0];
#pragma unroll
                for (int i = 1; i < 8; i++) { m0 = fmaxf(m0, v0[i]); m1 = fmaxf(m1, v1[i]); }
                m0 = fmaxf(m0, __shfl_xor_sync(0xffffffffu, m0, 1));
                m0 = fmaxf(m0, __shfl_xor_sync(0xffffffffu, m0, 2));
                m1 = fmaxf(m1, __shfl_xor_sync(0xffffffffu, m1, 1));
                m1 = fmaxf(m1, __shfl_xor_sync(0xffffffffu, m1, 2));
                const float cs = 0.08838834764831845f * 1.4426950408889634f;
                float s0 = 0.f, s1 = 0.f;
#pragma unroll
                for (int i = 0; i < 8; i++) {
                    v0[i] = exp2f((v0[i] - m0) * cs); s0 += v0[i];
                    v1[i] = exp2f((v1[i] - m1) * cs); s1 += v1[i];
                }
                s0 += __shfl_xor_sync(0xffffffffu, s0, 1);
                s0 += __shfl_xor_sync(0xffffffffu, s0, 2);
                s1 += __shfl_xor_sync(0xffffffffu, s1, 1);
                s1 += __shfl_xor_sync(0xffffffffu, s1, 2);
                const float i0 = 1.f / s0, i1 = 1.f / s1;
                uint32_t pf[8];
#pragma unroll
                for (int t = 0; t < 2; t++) {
                    pf[4 * t + 0] = pack_bf16(v0[4 * t + 0] * i0, v0[4 * t + 1] * i0);
                    pf[4 * t + 1] = pack_bf16(v1[4 * t + 0] * i1, v1[4 * t + 1] * i1);
                    pf[4 * t + 2] = pack_bf16(v0[4 * t + 2] * i0, v0[4 * t + 3] * i0);
                    pf[4 * t + 3] = pack_bf16(v1[4 * t + 2] * i1, v1[4 * t + 3] * i1);
                }
                float oc[64];
                wait_full(st);
                TL(12 + hh);
                wgmma_fence();
#pragma unroll
                for (int t = 0; t < 4; t++) {
                    const bool val = (t >> 1) == (hi ? 1 : 0);
                    const int tt = t & 1;
                    wgmma_m64n128k16_rs(oc, val ? pf[4 * tt + 0] : 0u, val ? pf[4 * tt + 1] : 0u, val ? pf[4 * tt + 2] : 0u, val ? pf[4 * tt + 3] : 0u,
                                        make_desc(sv + t * 2048, 8192, 1024), t > 0);
                }
                wgmma_commit();
                wgmma_wait<0>();
#pragma unroll
                for (int c = 0; c < 8; c++) {
                    const uint32_t r0 = pack_bf16(oc[8 * c + 0], oc[8 * c + 1]);
                    const uint32_t r1 = pack_bf16(oc[8 * c + 2], oc[8 * c + 3]);
                    const uint32_t r2 = pack_bf16(oc[8 * c + 4], oc[8 * c + 5]);
                    const uint32_t r3 = pack_bf16(oc[8 * c + 6], oc[8 * c + 7]);
                    const int row = warp * 16 + (lane & 7) + ((lane >> 3) & 1) * 8;
                    const int chunk = (c & 3) * 2 + (lane >> 4);
                    const uint32_t addr = so + (c >> 2) * 8192 + row * 128 + ((chunk ^ (row & 7)) << 4);
                    stmatrix_x4(addr, r0, r1, r2, r3);
                }
                fence_proxy_async_smem();
                asm volatile("bar.arrive %0, 160;" ::"r"(4 + w) : "memory");
                if (hh == 1) TL(11);
            }
            release(st);
            TL(2 + hh);
        }

        asm volatile("bar.sync %0, 128;" ::"r"(1 + w) : "memory");
        mainloop(acc, true);
        TL(6);

        {
            const int tile = (blk * 4 + m) * 4 + n2;
            uint4* base = reinterpret_cast<uint4*>(g_part) + (size_t)(tile * 4) * (128 * 64);
#pragma unroll
            for (int q = 0; q < 4; q++) {
                if (q != s2) {
                    uint4* p = base + (size_t)s2 * (128 * 64) + ((q * 2 + w) * 4) * 128 + wtid;
#pragma unroll
                    for (int i = 0; i < 4; i++)
                        p[i * 128] = make_uint4(pack_bf16(acc[q * 32 + 8 * i], acc[q * 32 + 8 * i + 1]), pack_bf16(acc[q * 32 + 8 * i + 2], acc[q * 32 + 8 * i + 3]),
                                                pack_bf16(acc[q * 32 + 8 * i + 4], acc[q * 32 + 8 * i + 5]), pack_bf16(acc[q * 32 + 8 * i + 6], acc[q * 32 + 8 * i + 7]));
                }
            }
            asm volatile("bar.sync 3, 256;" ::: "memory");
            TL(7);
            if (w == 0 && wtid == 0) {
                __threadfence();
                atomicAdd(&g_rflag[tile], 1u);
                unsigned int spins = 0;
                while (ld_acquire(&g_rflag[tile]) < 4u) {
                    if (++spins > (1u << 26)) break;
                }
            }
            asm volatile("bar.sync 3, 256;" ::: "memory");
            if (w == 1 && wtid == 0) {
                if (atomicAdd(&g_rcons[tile], 1u) == 3u) {
                    g_rcons[tile] = 0u;
                    g_rflag[tile] = 0u;
                }
            }
            TL(8);
            float r[32];
#pragma unroll
            for (int q = 0; q < 4; q++) {
                if (q == s2) {
#pragma unroll
                    for (int i = 0; i < 32; i++) r[i] = acc[q * 32 + i];
                }
            }
#pragma unroll
            for (int sp = 0; sp < 4; sp++) {
                if (sp != s2) {
                    const uint4* p = base + (size_t)sp * (128 * 64) + ((s2 * 2 + w) * 4) * 128 + wtid;
#pragma unroll
                    for (int i = 0; i < 4; i++) {
                        const uint4 t = __ldcg(p + i * 128);
                        r[8 * i] += bf_lo(t.x); r[8 * i + 1] += bf_hi(t.x); r[8 * i + 2] += bf_lo(t.y); r[8 * i + 3] += bf_hi(t.y);
                        r[8 * i + 4] += bf_lo(t.z); r[8 * i + 5] += bf_hi(t.z); r[8 * i + 6] += bf_lo(t.w); r[8 * i + 7] += bf_hi(t.w);
                    }
                }
            }
            const int row = m * 128 + w * 64 + warp * 16 + (lane >> 2);
            __nv_bfloat16* op = out + (size_t)row * 2048 + blk * 1024 + n2 * 256 + s2 * 64 + (lane & 3) * 2;
#pragma unroll
            for (int g = 0; g < 8; g++) {
                *reinterpret_cast<uint32_t*>(op + g * 8) = pack_bf16(r[4 * g], r[4 * g + 1]);
                *reinterpret_cast<uint32_t*>(op + 8 * 2048 + g * 8) = pack_bf16(r[4 * g + 2], r[4 * g + 3]);
            }
        }
        TL(9);
        asm volatile("barrier.cluster.arrive.release.aligned;\n\tbarrier.cluster.wait.acquire.aligned;" ::: "memory");
    }
}

typedef CUresult (*EncodeFn)(CUtensorMap*, CUtensorMapDataType, cuuint32_t, void*, const cuuint64_t*, const cuuint64_t*,
                             const cuuint32_t*, const cuuint32_t*, CUtensorMapInterleave, CUtensorMapSwizzle,
                             CUtensorMapL2promotion, CUtensorMapFloatOOBfill);

static void make_map(EncodeFn fn, CUtensorMap* map, const void* ptr, uint64_t rows, uint64_t cols, uint32_t box_rows) {
    cuuint64_t dims[2] = {cols, rows};
    cuuint64_t strides[1] = {cols * 2};
    cuuint32_t box[2] = {64, box_rows};
    cuuint32_t estr[2] = {1, 1};
    fn(map, CU_TENSOR_MAP_DATA_TYPE_BFLOAT16, 2, const_cast<void*>(ptr), dims, strides, box, estr,
       CU_TENSOR_MAP_INTERLEAVE_NONE, CU_TENSOR_MAP_SWIZZLE_128B, CU_TENSOR_MAP_L2_PROMOTION_L2_128B, CU_TENSOR_MAP_FLOAT_OOB_FILL_NONE);
}

static void kernel_launch_stream(void* const* d_in, const int* in_sizes, int n_in, void* d_out, int out_size, cudaStream_t stream) {
    static Maps maps;
    static bool ready = false;
    static void* cached[11];
    bool same = ready;
    for (int i = 0; i < 10 && same; i++) same = (cached[i] == d_in[i]);
    if (!same) {
        void* fnp = nullptr;
        cudaDriverEntryPointQueryResult qres;
        cudaGetDriverEntryPoint("cuTensorMapEncodeTiled", &fnp, cudaEnableDefault, &qres);
        EncodeFn fn = (EncodeFn)fnp;
        void* optr = nullptr;
        cudaGetSymbolAddress(&optr, g_o);
        for (int b = 0; b < 2; b++) {
            make_map(fn, &maps.x[b], d_in[5 * b + 0], 512, 1024, 128);
            make_map(fn, &maps.k[b], d_in[5 * b + 1], 16384, 128, 32);
            make_map(fn, &maps.v[b], d_in[5 * b + 2], 16384, 128, 32);
            make_map(fn, &maps.wq[b], d_in[5 * b + 3], 1024, 4096, 64);
            make_map(fn, &maps.wo[b], d_in[5 * b + 4], 4096, 1024, 64);
        }
        make_map(fn, &maps.o, optr, 1024, 4096, 64);
        cudaFuncSetAttribute(mha2_fused_kernel, cudaFuncAttributeMaxDynamicSharedMemorySize, SMEM_BYTES);
        for (int i = 0; i < 10; i++) cached[i] = d_in[i];
        ready = true;
    }
    mha2_fused_kernel<<<128, 384, SMEM_BYTES, stream>>>(maps,
        (const __nv_bfloat16*)d_in[1], (const __nv_bfloat16*)d_in[2],
        (const __nv_bfloat16*)d_in[6], (const __nv_bfloat16*)d_in[7],
        (__nv_bfloat16*)d_out);
}

extern "C" void kernel_launch(void* const* d_in, const int* in_sizes, int n_in, void* d_out, int out_size) {
    kernel_launch_stream(d_in, in_sizes, n_in, d_out, out_size, (cudaStream_t)0);
}
```
